```python
import torch

def _softmax(x, axis=-1):
    return torch.softmax(x, dim=axis)
def _gelu(x):
    return torch.nn.functional.gelu(x, approximate="tanh")
def _silu(x):
    return torch.nn.functional.silu(x)
def _sigmoid(x):
    return torch.sigmoid(x)
def _layernorm(x, axis=-1, eps=1e-5):
    m = x.mean(dim=axis, keepdim=True)
    v = x.var(dim=axis, keepdim=True, unbiased=False)
    return (x - m) / torch.sqrt(v + eps)
def _scatter_add(tgt, idx, src, axis=0):
    return tgt.clone().index_add_(axis, idx, src)
def _segment_sum(src, seg, n):
    out = torch.zeros((n,) + src.shape[1:], dtype=src.dtype)
    return out.index_add_(0, seg, src)
def _pad(x, pw):
    flat = tuple(v for pair in reversed(pw) for v in pair)
    return torch.nn.functional.pad(x, flat)

kernel_name = 'standalone__softmax_full_bidir__sampling'

def setup_inputs():

    _w = (lambda a: (lambda t: t.to(torch.bfloat16) if t.is_floating_point() else t)(torch.as_tensor(a)))
    B, H, Sq, Skv, Dh = 16, 32, 4, 4096, 128
    return {
        "q": _w((lambda *s: torch.randn(*s, dtype=torch.bfloat16) * 0.8)(B, H, Sq, Dh)),
        "k": _w((lambda *s: torch.randn(*s, dtype=torch.bfloat16) * 0.8)(B, H, Skv, Dh)),
        "v": _w((lambda *s: torch.randn(*s, dtype=torch.bfloat16) * 0.05)(B, H, Skv, Dh)),
    }

def reference(q, k, v):
    scale = q.shape[-1] ** -0.5
    scores = torch.einsum('bhqd,bhkd->bhqk', q, k) * scale
    attn = _softmax(scores, axis=-1)
    return torch.einsum('bhqk,bhkd->bhqd', attn, v)
```

```cpp
#include <cuda_runtime.h>
#include <cuda_bf16.h>
#include <cuda.h>
#include <stdint.h>

namespace {

constexpr int NHEADS = 512;
constexpr int SQ     = 4;
constexpr int SKV    = 4096;
constexpr int DH     = 128;

#define CFG_NSLOTS 3
#define CFG_R1 512
#define CFG_R2 128
#define CFG_TH 96
#define CFG_D 2
#define CFG_NCTA 132
#define CFG_HINT 1
#define CFG_POLL_NS 200
#define CFG_EAGER 264
#define CFG_DBG 0

constexpr int TILE_ROWS  = 128;
constexpr int TILE_BYTES = TILE_ROWS * DH * 2;
constexpr int HALF_BYTES = TILE_BYTES / 2;
constexpr int NSLOTS = CFG_NSLOTS;
constexpr int NCW = 8;
constexpr int NEW = 4;
constexpr int NTHREADS = 32 * (NCW + NEW + 1);

constexpr int R1 = CFG_R1, R2 = CFG_R2;
constexpr int P1 = SKV / R1;
constexpr int SPL = R1 / R2;
constexpr int TH = CFG_TH, DD = CFG_D;
constexpr int H1 = NHEADS - TH;
constexpr int NA1 = H1 * P1;
constexpr int NA  = NA1 + TH * (P1 - DD);
constexpr int NB  = TH * DD * SPL;
constexpr int NCHUNKS = NA + NB;
constexpr int NP_TAIL = (P1 - DD) + DD * SPL;
constexpr int PMAX = 16;
static_assert(P1 <= PMAX && NP_TAIL <= PMAX && P1 >= 2 && DD <= P1, "bad chunking");
static_assert(R1 % TILE_ROWS == 0 && R2 % TILE_ROWS == 0 && R1 % R2 == 0, "chunk must be whole tiles");

constexpr int JQ = 4;
constexpr int MQ_STRIDE = 132;
constexpr int MW_STRIDE = SQ * MQ_STRIDE;
constexpr int MBUF_BYTES = NCW * MW_STRIDE * 4 + NCW * SQ * 8;
constexpr int OWN_BYTES  = SQ * DH * 4 + SQ * 8;

constexpr int SM_TILES = 0;
constexpr int SM_Q     = SM_TILES + NSLOTS * TILE_BYTES;
constexpr int SM_MB    = SM_Q + NSLOTS * 1024;
constexpr int SM_OWN   = SM_MB + 2 * MBUF_BYTES;
constexpr int SM_META  = SM_OWN + JQ * OWN_BYTES;
constexpr int SM_JOB   = SM_META + NSLOTS * 16;
constexpr int SM_EPOCH = SM_JOB + JQ * 8;
constexpr int SM_BARS  = SM_EPOCH + 16;
constexpr int SM_TOTAL = SM_BARS + (2 * NSLOTS + 3 * JQ + 1) * 8;
constexpr int SMEM_BYTES = SM_TOTAL + 1024;
static_assert(MBUF_BYTES % 16 == 0 && OWN_BYTES % 16 == 0, "align");

constexpr int FLAG_FIRST = 1, FLAG_LAST = 2, FLAG_END = 4, FLAG_OWNER = 8;

__device__ float        g_partO[(size_t)NHEADS * PMAX * SQ * DH];
__device__ float2       g_partML[(size_t)NHEADS * SQ * PMAX];
__device__ unsigned int g_work;
__device__ unsigned int g_done;
__device__ unsigned int g_epoch;

__device__ __forceinline__ uint32_t smem_u32(const void* p) { return (uint32_t)__cvta_generic_to_shared(p); }
__device__ __forceinline__ void mbar_init(uint32_t bar, uint32_t cnt) {
    asm volatile("mbarrier.init.shared::cta.b64 [%0], %1;" :: "r"(bar), "r"(cnt) : "memory");
}
__device__ __forceinline__ void mbar_expect_tx(uint32_t bar, uint32_t bytes) {
    asm volatile("mbarrier.arrive.expect_tx.shared::cta.b64 _, [%0], %1;" :: "r"(bar), "r"(bytes) : "memory");
}
__device__ __forceinline__ void mbar_arrive(uint32_t bar) {
    asm volatile("mbarrier.arrive.shared::cta.b64 _, [%0];" :: "r"(bar) : "memory");
}
__device__ __forceinline__ bool mbar_try_wait(uint32_t bar, uint32_t parity) {
    uint32_t ok;
    asm volatile("{\n.reg .pred p;\nmbarrier.try_wait.parity.shared::cta.b64 p, [%1], %2;\nselp.u32 %0, 1, 0, p;\n}"
                 : "=r"(ok) : "r"(bar), "r"(parity) : "memory");
    return ok != 0;
}
__device__ __forceinline__ bool mbar_test_wait(uint32_t bar, uint32_t parity) {
    uint32_t ok;
    asm volatile("{\n.reg .pred p;\nmbarrier.test_wait.parity.shared::cta.b64 p, [%1], %2;\nselp.u32 %0, 1, 0, p;\n}"
                 : "=r"(ok) : "r"(bar), "r"(parity) : "memory");
    return ok != 0;
}
__device__ __forceinline__ void mbar_wait(uint32_t bar, uint32_t parity) {
    if (mbar_try_wait(bar, parity)) return;
    const long long t0 = clock64();
    while (!mbar_try_wait(bar, parity)) {
        if (clock64() - t0 > 4000000000LL) __trap();
    }
}
__device__ __forceinline__ void tma_load_2d(uint32_t dst, const CUtensorMap* tm, int c0, int c1, uint32_t bar, uint64_t pol) {
    asm volatile("cp.async.bulk.tensor.2d.shared::cluster.global.mbarrier::complete_tx::bytes.L2::cache_hint [%0], [%1, {%3, %4}], [%2], %5;"
                 :: "r"(dst), "l"(tm), "r"(bar), "r"(c0), "r"(c1), "l"(pol) : "memory");
}
__device__ __forceinline__ void bulk_load(uint32_t dst, const void* src, uint32_t bytes, uint32_t bar) {
    asm volatile("cp.async.bulk.shared::cluster.global.mbarrier::complete_tx::bytes [%0], [%1], %2, [%3];"
                 :: "r"(dst), "l"(src), "r"(bytes), "r"(bar) : "memory");
}
__device__ __forceinline__ void ldsm_x4(uint32_t (&r)[4], uint32_t addr) {
    asm volatile("ldmatrix.sync.aligned.m8n8.x4.shared.b16 {%0,%1,%2,%3}, [%4];"
                 : "=r"(r[0]), "=r"(r[1]), "=r"(r[2]), "=r"(r[3]) : "r"(addr) : "memory");
}
__device__ __forceinline__ void ldsm_x4_t(uint32_t (&r)[4], uint32_t addr) {
    asm volatile("ldmatrix.sync.aligned.m8n8.x4.trans.shared.b16 {%0,%1,%2,%3}, [%4];"
                 : "=r"(r[0]), "=r"(r[1]), "=r"(r[2]), "=r"(r[3]) : "r"(addr) : "memory");
}
__device__ __forceinline__ void mma_bf16(float (&d)[4], const uint32_t (&a)[4], uint32_t b0, uint32_t b1) {
    asm volatile("mma.sync.aligned.m16n8k16.row.col.f32.bf16.bf16.f32 {%0,%1,%2,%3}, {%4,%5,%6,%7}, {%8,%9}, {%0,%1,%2,%3};"
                 : "+f"(d[0]), "+f"(d[1]), "+f"(d[2]), "+f"(d[3])
                 : "r"(a[0]), "r"(a[1]), "r"(a[2]), "r"(a[3]), "r"(b0), "r"(b1));
}
__device__ __forceinline__ uint32_t movmatrix_t(uint32_t a) {
    uint32_t d;
    asm volatile("movmatrix.sync.aligned.m8n8.trans.b16 %0, %1;" : "=r"(d) : "r"(a));
    return d;
}
__device__ __forceinline__ uint32_t pack_bf16(float lo, float hi) {
    uint32_t d;
    asm("cvt.rn.bf16x2.f32 %0, %1, %2;" : "=r"(d) : "f"(hi), "f"(lo));
    return d;
}
__device__ __forceinline__ float ex2(float x) {
    float y;
    asm("ex2.approx.ftz.f32 %0, %1;" : "=f"(y) : "f"(x));
    return y;
}
__device__ __forceinline__ void named_bar_sync(int id, int nthreads) {
    asm volatile("bar.sync %0, %1;" :: "r"(id), "r"(nthreads) : "memory");
}
__device__ __forceinline__ unsigned atom_inc_relaxed(unsigned int* p) {
    unsigned o;
    asm volatile("atom.relaxed.gpu.global.add.u32 %0, [%1], 1;" : "=r"(o) : "l"(p) : "memory");
    return o;
}

__device__ __forceinline__ float tagf(float x, uint32_t tag) { return __uint_as_float((__float_as_uint(x) & ~1u) | tag); }
__device__ __forceinline__ void st_relaxed_v2(float* p, float x, float y) {
    asm volatile("st.relaxed.gpu.global.v2.f32 [%0], {%1, %2};" :: "l"(p), "f"(x), "f"(y) : "memory");
}
__device__ __forceinline__ float4 ld_relaxed_v4(const float* p) {
    float4 v;
    asm volatile("ld.relaxed.gpu.global.v4.f32 {%0,%1,%2,%3}, [%4];" : "=f"(v.x), "=f"(v.y), "=f"(v.z), "=f"(v.w) : "l"(p) : "memory");
    return v;
}
__device__ __forceinline__ float2 ld_relaxed_v2(const float* p) {
    float2 v;
    asm volatile("ld.relaxed.gpu.global.v2.f32 {%0,%1}, [%2];" : "=f"(v.x), "=f"(v.y) : "l"(p) : "memory");
    return v;
}

__global__ void __launch_bounds__(NTHREADS, 1)
attn_decode_kernel(const __grid_constant__ CUtensorMap tmK, const __grid_constant__ CUtensorMap tmV,
                   const __nv_bfloat16* __restrict__ q, __nv_bfloat16* __restrict__ out)
{
    extern __shared__ unsigned char smem_raw[];
    const uint32_t sbase = (smem_u32(smem_raw) + 1023u) & ~1023u;
    unsigned char* sptr = smem_raw + (sbase - smem_u32(smem_raw));

    const int warp = threadIdx.x >> 5, lane = threadIdx.x & 31;
    const uint32_t bar_full   = sbase + SM_BARS;
    const uint32_t bar_empty  = bar_full + NSLOTS * 8;
    const uint32_t bar_jstart = bar_empty + NSLOTS * 8;
    const uint32_t bar_jown   = bar_jstart + JQ * 8;
    const uint32_t bar_jfree  = bar_jown + JQ * 8;
    const uint32_t bar_epoch  = bar_jfree + JQ * 8;
    volatile uint32_t* s_epoch = reinterpret_cast<volatile uint32_t*>(sptr + SM_EPOCH);
    volatile int4* meta = reinterpret_cast<volatile int4*>(sptr + SM_META);
    volatile int2* jobq = reinterpret_cast<volatile int2*>(sptr + SM_JOB);

    if (threadIdx.x == NTHREADS - 32) {
        asm volatile("prefetch.tensormap [%0];" :: "l"(&tmK) : "memory");
        asm volatile("prefetch.tensormap [%0];" :: "l"(&tmV) : "memory");
        for (int s = 0; s < NSLOTS; s++) { mbar_init(bar_full + 8 * s, 1); mbar_init(bar_empty + 8 * s, NCW); }
        for (int s = 0; s < JQ; s++) { mbar_init(bar_jstart + 8 * s, 1); mbar_init(bar_jown + 8 * s, NCW); mbar_init(bar_jfree + 8 * s, NEW); }
        mbar_init(bar_epoch, 1);
        asm volatile("fence.mbarrier_init.release.cluster;" ::: "memory");
    }
    __syncthreads();

    const float SC = 0.08838834764831845f * 1.4426950408889634f;

    if (warp == NCW + NEW) {
        if (lane == 0) {
            uint64_t pol = 0;
            asm volatile("createpolicy.fractional.L2::evict_first.b64 %0, 1.0;" : "=l"(pol));
            int slot = 0; uint32_t phase = 1;
            unsigned c = blockIdx.x;
            int job = 0;
            while (c < (unsigned)NCHUNKS) {
                int head, pidx, nt, np, row;
                if (c < (unsigned)NA1) {
                    head = c / P1; pidx = c % P1; nt = R1 / TILE_ROWS; np = P1; row = pidx * R1;
                } else if (c < (unsigned)NA) {
                    const int c2 = c - NA1;
                    head = H1 + c2 / (P1 - DD); pidx = c2 % (P1 - DD); nt = R1 / TILE_ROWS; np = NP_TAIL; row = pidx * R1;
                } else {
                    const int c2 = c - NA, j = c2 % (DD * SPL);
                    head = H1 + c2 / (DD * SPL); pidx = (P1 - DD) + j; nt = R2 / TILE_ROWS; np = NP_TAIL;
                    row = (P1 - DD) * R1 + j * R2;
                }
                row += head * SKV;
                const bool owner = (pidx == np - 1);
                unsigned cn = 0;
                for (int i = 0; i < nt; i++, row += TILE_ROWS) {
                    if (i == nt - 1) {
                        cn = atom_inc_relaxed(&g_work);
                        if (owner) {
                            const int js = job % JQ;
                            mbar_wait(bar_jfree + 8 * js, ((job / JQ) & 1) ^ 1);
                            jobq[js].x = head; jobq[js].y = np | (c + CFG_EAGER >= (unsigned)NCHUNKS ? 256 : 0);
                            mbar_arrive(bar_jstart + 8 * js);
                            job++;
                        }
                    }
                    mbar_wait(bar_empty + 8 * slot, phase);
                    {
                        const uint32_t fb = bar_full + 8 * slot, dst = sbase + SM_TILES + slot * TILE_BYTES;
                        const int flags = (i == 0 ? FLAG_FIRST : 0) | (i == nt - 1 ? FLAG_LAST : 0) | (owner ? FLAG_OWNER : 0);
                        meta[slot].x = head; meta[slot].y = pidx; meta[slot].z = np; meta[slot].w = flags;
                        mbar_expect_tx(fb, TILE_BYTES + (i == 0 ? SQ * DH * 2 : 0));
                        tma_load_2d(dst, &tmK, 0, row, fb, pol);
                        tma_load_2d(dst + HALF_BYTES, &tmK, 64, row, fb, pol);
                        if (i == 0) bulk_load(sbase + SM_Q + slot * 1024, q + (size_t)head * SQ * DH, SQ * DH * 2, fb);
                    }
                    if (++slot == NSLOTS) { slot = 0; phase ^= 1; }
                    mbar_wait(bar_empty + 8 * slot, phase);
                    {
                        const uint32_t fb = bar_full + 8 * slot, dst = sbase + SM_TILES + slot * TILE_BYTES;
                        mbar_expect_tx(fb, TILE_BYTES);
                        tma_load_2d(dst, &tmV, 0, row, fb, pol);
                        tma_load_2d(dst + HALF_BYTES, &tmV, 64, row, fb, pol);
                    }
                    if (++slot == NSLOTS) { slot = 0; phase ^= 1; }
                }
                c = cn + gridDim.x;
            }
            {
                const int js = job % JQ;
                mbar_wait(bar_jfree + 8 * js, ((job / JQ) & 1) ^ 1);
                jobq[js].x = -1; jobq[js].y = 0;
                mbar_arrive(bar_jstart + 8 * js);
            }
            mbar_wait(bar_epoch, 0);
            if (atom_inc_relaxed(&g_done) == gridDim.x - 1) { g_work = 0; g_done = 0; g_epoch = *s_epoch + 1u; }
            mbar_wait(bar_empty + 8 * slot, phase);
            meta[slot].w = FLAG_END;
            mbar_arrive(bar_full + 8 * slot);
        }
    } else if (warp < NCW) {
        const int g = lane >> 2, t = lane & 3, r8 = lane & 7;
        const uint32_t kOff = (uint32_t)((warp * 16 + r8 + ((lane >> 3) & 1) * 8) * 128 + (((lane >> 4) ^ r8) << 4));
        const uint32_t vOff = (uint32_t)((warp * 16 + r8 + (lane >> 4) * 8) * 128 + ((((lane >> 3) & 1) ^ r8) << 4));
        uint32_t qf[8][2];
        float o[8][4];
        float m0 = 0.f, m1 = 0.f, l0 = 0.f, l1 = 0.f;
#pragma unroll
        for (int j = 0; j < 8; j++) { qf[j][0] = qf[j][1] = 0u; o[j][0] = o[j][1] = o[j][2] = o[j][3] = 0.f; }
        int slot = 0; uint32_t phase = 0;
        int job = 0, nchunk = 0;
        uint32_t tag = 2u;
        while (true) {
            mbar_wait(bar_full + 8 * slot, phase);
            const int flags = meta[slot].w;
            if (flags & FLAG_END) break;
            const int head = meta[slot].x, pidx = meta[slot].y;
            const uint32_t kb = sbase + SM_TILES + slot * TILE_BYTES;
            uint32_t kf[8][4];
#pragma unroll
            for (int j = 0; j < 8; j++)
                ldsm_x4(kf[j], kb + (j >> 2) * HALF_BYTES + (kOff ^ (uint32_t)(((2 * j) & 7) << 4)));
            if (flags & FLAG_FIRST) {
                const uint32_t* qs = reinterpret_cast<const uint32_t*>(sptr + SM_Q + slot * 1024);
#pragma unroll
                for (int j = 0; j < 8; j++) {
                    qf[j][0] = (g < SQ) ? qs[g * 64 + j * 8 + t] : 0u;
                    qf[j][1] = (g < SQ) ? qs[g * 64 + j * 8 + 4 + t] : 0u;
                    o[j][0] = o[j][1] = o[j][2] = o[j][3] = 0.f;
                }
                m0 = m1 = -INFINITY; l0 = l1 = 0.f;
            }
            __syncwarp();
            if (lane == 0) mbar_arrive(bar_empty + 8 * slot);
            if (++slot == NSLOTS) { slot = 0; phase ^= 1; }

            float sa[4] = {0.f, 0.f, 0.f, 0.f}, sb[4] = {0.f, 0.f, 0.f, 0.f};
#pragma unroll
            for (int j = 0; j < 8; j += 2) {
                mma_bf16(sa, kf[j], qf[j][0], qf[j][1]);
                mma_bf16(sb, kf[j + 1], qf[j + 1][0], qf[j + 1][1]);
            }
            const float s0 = sa[0] + sb[0], s1 = sa[1] + sb[1], s2 = sa[2] + sb[2], s3 = sa[3] + sb[3];
            float t0 = fmaxf(s0, s2), t1 = fmaxf(s1, s3);
#pragma unroll
            for (int x = 4; x <= 16; x <<= 1) {
                t0 = fmaxf(t0, __shfl_xor_sync(0xffffffffu, t0, x));
                t1 = fmaxf(t1, __shfl_xor_sync(0xffffffffu, t1, x));
            }
            const float n0 = fmaxf(m0, t0 * SC), n1 = fmaxf(m1, t1 * SC);
            const float a0 = ex2(m0 - n0), a1 = ex2(m1 - n1);
            m0 = n0; m1 = n1;
            const float p0 = ex2(fmaf(s0, SC, -n0)), p1 = ex2(fmaf(s1, SC, -n1));
            const float p2 = ex2(fmaf(s2, SC, -n0)), p3 = ex2(fmaf(s3, SC, -n1));
            l0 = fmaf(l0, a0, p0 + p2);
            l1 = fmaf(l1, a1, p1 + p3);
            const uint32_t b0 = movmatrix_t(pack_bf16(p0, p1));
            const uint32_t b1 = movmatrix_t(pack_bf16(p2, p3));

            mbar_wait(bar_full + 8 * slot, phase);
            const uint32_t vb = sbase + SM_TILES + slot * TILE_BYTES;
            uint32_t vf[8][4];
#pragma unroll
            for (int j = 0; j < 8; j++)
                ldsm_x4_t(vf[j], vb + (j >> 2) * HALF_BYTES + (vOff ^ (uint32_t)(((2 * j) & 7) << 4)));
            __syncwarp();
            if (lane == 0) mbar_arrive(bar_empty + 8 * slot);
            if (++slot == NSLOTS) { slot = 0; phase ^= 1; }
#pragma unroll
            for (int j = 0; j < 8; j++) {
                o[j][0] *= a0; o[j][1] *= a1; o[j][2] *= a0; o[j][3] *= a1;
                mma_bf16(o[j], vf[j], b0, b1);
            }

            if (flags & FLAG_LAST) {
                float r0 = l0, r1 = l1;
#pragma unroll
                for (int x = 4; x <= 16; x <<= 1) {
                    r0 += __shfl_xor_sync(0xffffffffu, r0, x);
                    r1 += __shfl_xor_sync(0xffffffffu, r1, x);
                }
                float* mbuf = reinterpret_cast<float*>(sptr + SM_MB + (nchunk & 1) * MBUF_BYTES);
                float* mlbuf = mbuf + NCW * MW_STRIDE;
                if (t < 2) {
                    float* mo = mbuf + warp * MW_STRIDE;
#pragma unroll
                    for (int j = 0; j < 8; j++) {
                        mo[(2 * t) * MQ_STRIDE + j * 16 + g]         = o[j][0];
                        mo[(2 * t + 1) * MQ_STRIDE + j * 16 + g]     = o[j][1];
                        mo[(2 * t) * MQ_STRIDE + j * 16 + g + 8]     = o[j][2];
                        mo[(2 * t + 1) * MQ_STRIDE + j * 16 + g + 8] = o[j][3];
                    }
                    if (g == 0) *reinterpret_cast<float4*>(mlbuf + warp * 8 + t * 4) = make_float4(m0, r0, m1, r1);
                }
                named_bar_sync(2, NCW * 32);
                {
                    const int qi = threadIdx.x >> 6, d2 = (threadIdx.x & 63) * 2;
                    float2 wml[NCW];
                    float M = -INFINITY;
#pragma unroll
                    for (int w = 0; w < NCW; w++) {
                        wml[w] = *reinterpret_cast<const float2*>(mlbuf + w * 8 + qi * 2);
                        M = fmaxf(M, wml[w].x);
                    }
                    if (tag > 1u) { mbar_wait(bar_epoch, 0); tag = (*s_epoch + 1u) & 1u; }
                    M = tagf(M, tag);
                    float L = 0.f, ax = 0.f, ay = 0.f;
#pragma unroll
                    for (int w = 0; w < NCW; w++) {
                        const float sc = ex2(wml[w].x - M);
                        const float2 v = *reinterpret_cast<const float2*>(mbuf + w * MW_STRIDE + qi * MQ_STRIDE + d2);
                        L = fmaf(wml[w].y, sc, L);
                        ax = fmaf(v.x, sc, ax); ay = fmaf(v.y, sc, ay);
                    }
                    if (flags & FLAG_OWNER) {
                        float* own = reinterpret_cast<float*>(sptr + SM_OWN + (job % JQ) * OWN_BYTES);
                        *reinterpret_cast<float2*>(own + qi * DH + d2) = make_float2(ax, ay);
                        if (d2 == 0) *reinterpret_cast<float2*>(own + SQ * DH + qi * 2) = make_float2(M, L);
                        __syncwarp();
                        if (lane == 0) mbar_arrive(bar_jown + 8 * (job % JQ));
                        job++;
                    } else {
                        st_relaxed_v2(g_partO + (((size_t)head * PMAX + pidx) * SQ + qi) * DH + d2, tagf(ax, tag), tagf(ay, tag));
                        if (d2 == 0) st_relaxed_v2(reinterpret_cast<float*>(g_partML + ((size_t)head * SQ + qi) * PMAX + pidx), M, tagf(L, tag));
                    }
                }
                nchunk++;
            }
        }
    } else {
        const int e = threadIdx.x - NCW * 32;
        const int qi = e >> 5;
        const int d4 = lane * 4;
        if (e == 0) {
            uint32_t ep;
            asm volatile("ld.relaxed.gpu.global.u32 %0, [%1];" : "=r"(ep) : "l"(&g_epoch) : "memory");
            *s_epoch = ep;
            mbar_arrive(bar_epoch);
        }
        mbar_wait(bar_epoch, 0);
        const uint32_t tag = (*s_epoch + 1u) & 1u;
        for (int k = 0;; k++) {
            const int js = k % JQ; const uint32_t jph = (k / JQ) & 1;
            mbar_wait(bar_jstart + 8 * js, jph);
            const int head = jobq[js].x, np = jobq[js].y & 255;
            const bool eager_ok = (jobq[js].y & 256) != 0;
            if (head < 0) break;
            const float* pml = reinterpret_cast<const float*>(g_partML + ((size_t)head * SQ + qi) * PMAX + (lane & (PMAX - 1)));
            const float* po  = g_partO + ((size_t)head * PMAX * SQ + qi) * DH + d4;
            float4 v[PMAX - 1];
#pragma unroll
            for (int u = 0; u < PMAX - 1; u++) v[u] = make_float4(0.f, 0.f, 0.f, 0.f);
            float2 pm = make_float2(-INFINITY, 0.f);
            uint32_t pending = (1u << (np - 1)) - 1u;
            const long long tstart = clock64();
            while (true) {
                if ((pending >> lane) & 1u) pm = ld_relaxed_v2(pml);
                uint32_t fetch = pending;
                const bool urgent = eager_ok && __all_sync(0xffffffffu, mbar_test_wait(bar_jown + 8 * js, jph));
                if (!urgent) {
                    fetch &= __ballot_sync(0xffffffffu,
                        ((__float_as_uint(pm.x) & 1u) == tag) && ((__float_as_uint(pm.y) & 1u) == tag));
                }
#pragma unroll
                for (int u = 0; u < PMAX - 1; u++)
                    if ((fetch >> u) & 1u) v[u] = ld_relaxed_v4(po + (size_t)u * (SQ * DH));
                const uint32_t mlok = fetch & __ballot_sync(0xffffffffu,
                    ((__float_as_uint(pm.x) & 1u) == tag) && ((__float_as_uint(pm.y) & 1u) == tag));
                uint32_t bad = 0;
#pragma unroll
                for (int u = 0; u < PMAX - 1; u++) {
                    const uint32_t x = (__float_as_uint(v[u].x) ^ tag) | (__float_as_uint(v[u].y) ^ tag) |
                                       (__float_as_uint(v[u].z) ^ tag) | (__float_as_uint(v[u].w) ^ tag);
                    bad |= (x & 1u) << u;
                }
                bad = __reduce_or_sync(0xffffffffu, bad);
                pending &= (bad | ~mlok);
                if (pending == 0u) break;
                if (clock64() - tstart > 4000000000LL) __trap();
                __nanosleep(CFG_POLL_NS);
            }
            float Mo = (lane < np - 1) ? pm.x : -INFINITY;
#pragma unroll
            for (int x = 1; x < PMAX; x <<= 1) Mo = fmaxf(Mo, __shfl_xor_sync(0xffffffffu, Mo, x));
            Mo = __shfl_sync(0xffffffffu, Mo, 0);
            const float sc = (lane < np - 1) ? ex2(pm.x - Mo) : 0.f;
            float Lo = pm.y * sc;
#pragma unroll
            for (int x = 1; x < PMAX; x <<= 1) Lo += __shfl_xor_sync(0xffffffffu, Lo, x);
            Lo = __shfl_sync(0xffffffffu, Lo, 0);
            float4 acc = make_float4(0.f, 0.f, 0.f, 0.f);
#pragma unroll
            for (int u = 0; u < PMAX - 1; u++) {
                const float s = __shfl_sync(0xffffffffu, sc, u);
                acc.x = fmaf(v[u].x, s, acc.x); acc.y = fmaf(v[u].y, s, acc.y);
                acc.z = fmaf(v[u].z, s, acc.z); acc.w = fmaf(v[u].w, s, acc.w);
            }
            mbar_wait(bar_jown + 8 * js, jph);
            const float* own = reinterpret_cast<const float*>(sptr + SM_OWN + js * OWN_BYTES);
            const float4 ov = *reinterpret_cast<const float4*>(own + qi * DH + d4);
            const float2 oml = *reinterpret_cast<const float2*>(own + SQ * DH + qi * 2);
            __syncwarp();
            if (lane == 0) mbar_arrive(bar_jfree + 8 * js);
            const float M = fmaxf(Mo, oml.x);
            const float fa = ex2(Mo - M), fb = ex2(oml.x - M);
            const float inv = 1.0f / fmaf(Lo, fa, oml.y * fb);
            const float ca = fa * inv, cb = fb * inv;
            uint2 pk;
            pk.x = pack_bf16(fmaf(acc.x, ca, ov.x * cb), fmaf(acc.y, ca, ov.y * cb));
            pk.y = pack_bf16(fmaf(acc.z, ca, ov.z * cb), fmaf(acc.w, ca, ov.w * cb));
            *reinterpret_cast<uint2*>(out + ((size_t)head * SQ + qi) * DH + d4) = pk;
        }
    }
}

typedef CUresult (*EncodeTiledFn)(CUtensorMap*, CUtensorMapDataType, cuuint32_t, void*, const cuuint64_t*,
                                  const cuuint64_t*, const cuuint32_t*, const cuuint32_t*, CUtensorMapInterleave,
                                  CUtensorMapSwizzle, CUtensorMapL2promotion, CUtensorMapFloatOOBfill);

void make_map(EncodeTiledFn enc, CUtensorMap* m, void* p) {
    cuuint64_t dims[2]    = {(cuuint64_t)DH, (cuuint64_t)NHEADS * SKV};
    cuuint64_t strides[1] = {(cuuint64_t)DH * 2};
    cuuint32_t box[2]     = {64, (cuuint32_t)TILE_ROWS};
    cuuint32_t es[2]      = {1, 1};
    enc(m, CU_TENSOR_MAP_DATA_TYPE_BFLOAT16, 2, p, dims, strides, box, es, CU_TENSOR_MAP_INTERLEAVE_NONE,
        CU_TENSOR_MAP_SWIZZLE_128B, CU_TENSOR_MAP_L2_PROMOTION_L2_256B, CU_TENSOR_MAP_FLOAT_OOB_FILL_NONE);
}

}

extern "C" void kernel_launch(void* const* d_in, const int* in_sizes, int n_in, void* d_out, int out_size) {
    (void)in_sizes; (void)n_in; (void)out_size;
    static EncodeTiledFn enc = nullptr;
    static int nsm = 0;
    if (!enc) {
        cudaDriverEntryPointQueryResult qr;
        void* fn = nullptr;
        cudaGetDriverEntryPoint("cuTensorMapEncodeTiled", &fn, cudaEnableDefault, &qr);
        enc = (EncodeTiledFn)fn;
        cudaFuncSetAttribute(attn_decode_kernel, cudaFuncAttributeMaxDynamicSharedMemorySize, SMEM_BYTES);
        int dev = 0;
        cudaGetDevice(&dev);
        cudaDeviceGetAttribute(&nsm, cudaDevAttrMultiProcessorCount, dev);
    }
    CUtensorMap tmK, tmV;
    make_map(enc, &tmK, d_in[1]);
    make_map(enc, &tmV, d_in[2]);
    int grid = nsm < CFG_NCTA ? nsm : CFG_NCTA;
    attn_decode_kernel<<<grid, NTHREADS, SMEM_BYTES>>>(tmK, tmV, (const __nv_bfloat16*)d_in[0], (__nv_bfloat16*)d_out);
}
```

```cpp
#include <cuda_runtime.h>
#include <cuda_bf16.h>
#include <cuda.h>
#include <stdint.h>

namespace {

constexpr int NHEADS = 512;
constexpr int SQ     = 4;
constexpr int SKV    = 4096;
constexpr int DH     = 128;

constexpr int TILE_ROWS  = 128;
constexpr int TILE_BYTES = TILE_ROWS * DH * 2;
constexpr int HALF_BYTES = TILE_BYTES / 2;
constexpr int TPH    = SKV / TILE_ROWS;
constexpr int NSLOTS = 4;
constexpr int WIN    = 2;
constexpr int NCW = 8;
constexpr int NEW = 8;
constexpr int NTHREADS = 32 * (NCW + NEW + 1);
constexpr int MAX_CTA = 132;
#define GAP_FIXED_NS 1590.0

constexpr int NR   = TPH - 1;
constexpr int TH   = 500;
constexpr int GAP  = 12;
constexpr int HD0  = NHEADS - GAP - TH;
constexpr int NA1  = HD0 * (NR + 1);
constexpr int NA2  = NA1 + TH * NR;
constexpr int NA   = NA2 + GAP * (NR + 1);
constexpr int NCHUNKS = NA + TH;
constexpr int LAG  = 480;
constexpr int LAG_END = 420, HEADS_END = 20;
constexpr int RING = 32;
constexpr int HREC = (NR + 2) / 2;
static_assert(HD0 >= 0 && LAG_END <= TH && LAG <= TH + HEADS_END * NR && LAG < RING * NR && LAG_END < RING * NR &&
              NHEADS % (2 * RING) == 0 && HREC <= 16 && 2 * MAX_CTA <= LAG_END && 2 * MAX_CTA <= RING * NR &&
              WIN + 1 <= NSLOTS, "bad schedule");

constexpr int JQ = 4;
constexpr int REC_BYTES  = SQ * DH * 4 + SQ * 8;
constexpr int REC_FLOATS = 544;

constexpr int SM_TILES = 0;
constexpr int SM_X     = SM_TILES + NSLOTS * TILE_BYTES;
constexpr int XS_BYTES = 1024 + REC_BYTES + 16 + 16;
constexpr int SM_PB    = SM_X + NSLOTS * XS_BYTES;
constexpr int SM_WM    = SM_PB + NCW * 32 * 8;
constexpr int SM_WS    = SM_WM + NCW * SQ * 4;
constexpr int SM_CX    = SM_WS + NCW * SQ * 4;
constexpr int SM_META  = SM_CX + REC_BYTES;
constexpr int SM_JOB   = SM_META + NSLOTS * 16;
constexpr int SM_EPOCH = SM_JOB + JQ * 4;
constexpr int SM_BARS  = SM_EPOCH + 16;
constexpr int SM_TOTAL = SM_BARS + (2 * NSLOTS + 2 * JQ + 1) * 8;
constexpr int SMEM_BYTES = SM_TOTAL + 1024;
static_assert(REC_BYTES % 16 == 0 && XS_BYTES % 16 == 0 && SM_BARS % 8 == 0, "align");

constexpr int FLAG_END = 4, FLAG_EXTRA = 8, FLAG_FINAL = 16;

__device__ __align__(128) float g_ring[(size_t)RING * NR * REC_FLOATS];
__device__ __align__(128) float g_comb[(size_t)NHEADS * REC_FLOATS];
__device__ __align__(16) unsigned int g_coll[NHEADS * 4];
__device__ unsigned int g_work;
__device__ unsigned int g_done;
__device__ unsigned int g_epoch;

__device__ __forceinline__ uint32_t smem_u32(const void* p) { return (uint32_t)__cvta_generic_to_shared(p); }
__device__ __forceinline__ void mbar_init(uint32_t bar, uint32_t cnt) {
    asm volatile("mbarrier.init.shared::cta.b64 [%0], %1;" :: "r"(bar), "r"(cnt) : "memory");
}
__device__ __forceinline__ void mbar_expect_tx(uint32_t bar, uint32_t bytes) {
    asm volatile("mbarrier.arrive.expect_tx.shared::cta.b64 _, [%0], %1;" :: "r"(bar), "r"(bytes) : "memory");
}
__device__ __forceinline__ void mbar_arrive(uint32_t bar) {
    asm volatile("mbarrier.arrive.shared::cta.b64 _, [%0];" :: "r"(bar) : "memory");
}
__device__ __forceinline__ bool mbar_try_wait(uint32_t bar, uint32_t parity) {
    uint32_t ok;
    asm volatile("{\n.reg .pred p;\nmbarrier.try_wait.parity.shared::cta.b64 p, [%1], %2;\nselp.u32 %0, 1, 0, p;\n}"
                 : "=r"(ok) : "r"(bar), "r"(parity) : "memory");
    return ok != 0;
}
constexpr long long SPIN_LIMIT = 4000000000LL;
__device__ __forceinline__ void mbar_wait(uint32_t bar, uint32_t parity) {
    if (mbar_try_wait(bar, parity)) return;
    const long long t0 = clock64();
    while (!mbar_try_wait(bar, parity)) {
        if (clock64() - t0 > SPIN_LIMIT) __trap();
    }
}
__device__ __forceinline__ void tma_load_2d(uint32_t dst, const CUtensorMap* tm, int c0, int c1, uint32_t bar, uint64_t pol) {
    asm volatile("cp.async.bulk.tensor.2d.shared::cluster.global.mbarrier::complete_tx::bytes.L2::cache_hint [%0], [%1, {%3, %4}], [%2], %5;"
                 :: "r"(dst), "l"(tm), "r"(bar), "r"(c0), "r"(c1), "l"(pol) : "memory");
}
__device__ __forceinline__ void bulk_load(uint32_t dst, const void* src, uint32_t bytes, uint32_t bar) {
    asm volatile("cp.async.bulk.shared::cluster.global.mbarrier::complete_tx::bytes [%0], [%1], %2, [%3];"
                 :: "r"(dst), "l"(src), "r"(bytes), "r"(bar) : "memory");
}
__device__ __forceinline__ void ldsm_x4(uint32_t (&r)[4], uint32_t addr) {
    asm volatile("ldmatrix.sync.aligned.m8n8.x4.shared.b16 {%0,%1,%2,%3}, [%4];"
                 : "=r"(r[0]), "=r"(r[1]), "=r"(r[2]), "=r"(r[3]) : "r"(addr) : "memory");
}
__device__ __forceinline__ void ldsm_x4_t(uint32_t (&r)[4], uint32_t addr) {
    asm volatile("ldmatrix.sync.aligned.m8n8.x4.trans.shared.b16 {%0,%1,%2,%3}, [%4];"
                 : "=r"(r[0]), "=r"(r[1]), "=r"(r[2]), "=r"(r[3]) : "r"(addr) : "memory");
}
__device__ __forceinline__ void mma_bf16(float (&d)[4], const uint32_t (&a)[4], uint32_t b0, uint32_t b1) {
    asm volatile("mma.sync.aligned.m16n8k16.row.col.f32.bf16.bf16.f32 {%0,%1,%2,%3}, {%4,%5,%6,%7}, {%8,%9}, {%0,%1,%2,%3};"
                 : "+f"(d[0]), "+f"(d[1]), "+f"(d[2]), "+f"(d[3])
                 : "r"(a[0]), "r"(a[1]), "r"(a[2]), "r"(a[3]), "r"(b0), "r"(b1));
}
__device__ __forceinline__ uint32_t movmatrix_t(uint32_t a) {
    uint32_t d;
    asm volatile("movmatrix.sync.aligned.m8n8.trans.b16 %0, %1;" : "=r"(d) : "r"(a));
    return d;
}
__device__ __forceinline__ uint32_t pack_bf16(float lo, float hi) {
    uint32_t d;
    asm("cvt.rn.bf16x2.f32 %0, %1, %2;" : "=r"(d) : "f"(hi), "f"(lo));
    return d;
}
__device__ __forceinline__ float ex2(float x) {
    float y;
    asm("ex2.approx.ftz.f32 %0, %1;" : "=f"(y) : "f"(x));
    return y;
}
__device__ __forceinline__ void named_bar_sync(int id, int nthreads) {
    asm volatile("bar.sync %0, %1;" :: "r"(id), "r"(nthreads) : "memory");
}
__device__ __forceinline__ unsigned atom_inc_relaxed(unsigned int* p) {
    unsigned o;
    asm volatile("atom.relaxed.gpu.global.add.u32 %0, [%1], 1;" : "=r"(o) : "l"(p) : "memory");
    return o;
}
__device__ __forceinline__ unsigned long long global_ns() {
    unsigned long long t;
    asm volatile("mov.u64 %0, %globaltimer;" : "=l"(t));
    return t;
}
__device__ __forceinline__ uint32_t fbits(float x) { return __float_as_uint(x); }
__device__ __forceinline__ float tagf(float x, uint32_t tag) { return __uint_as_float((fbits(x) & ~1u) | tag); }
__device__ __forceinline__ float4 untag(const float4& v) {
    return make_float4(tagf(v.x, 0u), tagf(v.y, 0u), tagf(v.z, 0u), tagf(v.w, 0u));
}
__device__ __forceinline__ uint32_t tag_bad(const float4& v, uint32_t tag) {
    return ((fbits(v.x) ^ tag) | (fbits(v.y) ^ tag) | (fbits(v.z) ^ tag) | (fbits(v.w) ^ tag)) & 1u;
}
__device__ __forceinline__ void st_relaxed_u32(unsigned int* p, uint32_t x) {
    asm volatile("st.relaxed.gpu.global.u32 [%0], %1;" :: "l"(p), "r"(x) : "memory");
}
__device__ __forceinline__ void st_relaxed_v4(float* p, float x, float y, float z, float w) {
    asm volatile("st.relaxed.gpu.global.v4.f32 [%0], {%1, %2, %3, %4};" :: "l"(p), "f"(x), "f"(y), "f"(z), "f"(w) : "memory");
}
__device__ __forceinline__ uint32_t ld_relaxed_u32(const unsigned int* p) {
    uint32_t v;
    asm volatile("ld.relaxed.gpu.global.u32 %0, [%1];" : "=r"(v) : "l"(p) : "memory");
    return v;
}
__device__ __forceinline__ float4 ld_relaxed_v4(const float* p) {
    float4 v;
    asm volatile("ld.relaxed.gpu.global.v4.f32 {%0,%1,%2,%3}, [%4];" : "=f"(v.x), "=f"(v.y), "=f"(v.z), "=f"(v.w) : "l"(p) : "memory");
    return v;
}

__device__ __forceinline__ void decode_a(int c, int& head, int& tile, int& cnt) {
    if (c < NA1)      { cnt = NR + 1; head = c / (NR + 1); tile = c % (NR + 1); }
    else if (c < NA2) { cnt = NR;     head = HD0 + (c - NA1) / NR; tile = (c - NA1) % NR; }
    else              { cnt = NR + 1; head = HD0 + TH + (c - NA2) / (NR + 1); tile = (c - NA2) % (NR + 1); }
}
__device__ __forceinline__ bool is_deferred(int head) { return head >= HD0 && head < HD0 + TH; }
__device__ __forceinline__ uint32_t ring_tag(int head) { return (uint32_t)(head / RING + 1) & 1u; }

__global__ void __launch_bounds__(NTHREADS, 1)
attn_decode_kernel(const __grid_constant__ CUtensorMap tmK, const __grid_constant__ CUtensorMap tmV,
                   const __nv_bfloat16* __restrict__ q, __nv_bfloat16* __restrict__ out, const unsigned gap_ns)
{
    extern __shared__ unsigned char smem_raw[];
    const uint32_t sbase = (smem_u32(smem_raw) + 1023u) & ~1023u;
    unsigned char* sptr = smem_raw + (sbase - smem_u32(smem_raw));

    const int warp = threadIdx.x >> 5, lane = threadIdx.x & 31;
    const uint32_t bar_full  = sbase + SM_BARS;
    const uint32_t bar_empty = bar_full + NSLOTS * 8;
    const uint32_t bar_jfull = bar_empty + NSLOTS * 8;
    const uint32_t bar_jfree = bar_jfull + JQ * 8;
    const uint32_t bar_epoch = bar_jfree + JQ * 8;
    volatile uint32_t* s_epoch = reinterpret_cast<volatile uint32_t*>(sptr + SM_EPOCH);
    volatile int4* meta = reinterpret_cast<volatile int4*>(sptr + SM_META);
    volatile int* jobq = reinterpret_cast<volatile int*>(sptr + SM_JOB);

    uint64_t pol = 0;
    if (threadIdx.x == NTHREADS - 32) {
        mbar_init(bar_full, 1);
        mbar_init(bar_full + 8, 1);
        asm volatile("fence.mbarrier_init.release.cluster;" ::: "memory");
        asm volatile("createpolicy.fractional.L2::evict_first.b64 %0, 1.0;" : "=l"(pol));
        int head, tile, cnt;
        decode_a((int)blockIdx.x, head, tile, cnt);
        const int row = head * SKV + tile * TILE_ROWS;
        meta[0].x = head; meta[0].y = tile; meta[0].w = (tile == NR) ? FLAG_EXTRA : 0;
        mbar_expect_tx(bar_full, TILE_BYTES + SQ * DH * 2);
        tma_load_2d(sbase + SM_TILES, &tmK, 0, row, bar_full, pol);
        tma_load_2d(sbase + SM_TILES + HALF_BYTES, &tmK, 64, row, bar_full, pol);
        mbar_expect_tx(bar_full + 8, TILE_BYTES);
        tma_load_2d(sbase + SM_TILES + TILE_BYTES, &tmV, 0, row, bar_full + 8, pol);
        tma_load_2d(sbase + SM_TILES + TILE_BYTES + HALF_BYTES, &tmV, 64, row, bar_full + 8, pol);
        bulk_load(sbase + SM_X, q + (size_t)head * SQ * DH, SQ * DH * 2, bar_full);
        for (int s = 2; s < NSLOTS; s++) mbar_init(bar_full + 8 * s, 1);
        for (int s = 0; s < NSLOTS; s++) mbar_init(bar_empty + 8 * s, NCW);
        for (int s = 0; s < JQ; s++) { mbar_init(bar_jfull + 8 * s, 1); mbar_init(bar_jfree + 8 * s, NEW); }
        mbar_init(bar_epoch, 1);
        asm volatile("fence.mbarrier_init.release.cluster;" ::: "memory");
    }
    __syncthreads();

    const float SC = 0.08838834764831845f * 1.4426950408889634f;

    if (warp == NCW + NEW) {
        if (lane == 0) {
            int nissued = 2;
            int job = 0;
            unsigned c = blockIdx.x + gridDim.x;
            while (c < (unsigned)NCHUNKS) {
                int head, tile, kind = 0;
                if (c < (unsigned)NA) {
                    int cnt;
                    decode_a((int)c, head, tile, cnt);
                    if (tile == NR) kind = FLAG_EXTRA;
                } else {
                    head = HD0 + ((int)c - NA); tile = NR; kind = FLAG_FINAL;
                }
#pragma unroll
                for (int z = 0; z < 2; z++) {
                    const int cc = (int)c - (z == 0 ? LAG : LAG_END);
                    if (cc >= 0 && cc < NA) {
                        int h2, t2, cnt2;
                        decode_a(cc, h2, t2, cnt2);
                        if (t2 == cnt2 - 1 && ((h2 >= NHEADS - HEADS_END) == (z == 1))) {
                            const int js = job % JQ;
                            mbar_wait(bar_jfree + 8 * js, ((job / JQ) & 1) ^ 1);
                            jobq[js] = h2;
                            mbar_arrive(bar_jfull + 8 * js);
                            job++;
                        }
                    }
                }
                const bool chk = (kind == 0) && head >= RING;
                const int row = head * SKV + tile * TILE_ROWS;
                unsigned long long tk = 0;
#pragma unroll
                for (int i = 0; i < 2; i++) {
                    const int slot = nissued % NSLOTS;
                    if (nissued > WIN) {
                        const int prev = nissued - WIN;
                        mbar_wait(bar_full + 8 * (prev % NSLOTS), (prev / NSLOTS) & 1);
                    }
                    mbar_wait(bar_empty + 8 * slot, ((nissued / NSLOTS) & 1) ^ 1);
                    const uint32_t fb = bar_full + 8 * slot, dst = sbase + SM_TILES + slot * TILE_BYTES;
                    if (i == 0) {
                        const uint32_t xb = sbase + SM_X + slot * XS_BYTES;
                        meta[slot].x = head; meta[slot].y = tile; meta[slot].w = kind;
                        mbar_expect_tx(fb, TILE_BYTES + SQ * DH * 2 + (kind == FLAG_FINAL ? REC_BYTES : 0) + (chk ? 16 : 0));
                        tma_load_2d(dst, &tmK, 0, row, fb, pol);
                        tma_load_2d(dst + HALF_BYTES, &tmK, 64, row, fb, pol);
                        bulk_load(xb, q + (size_t)head * SQ * DH, SQ * DH * 2, fb);
                        if (kind == FLAG_FINAL) bulk_load(xb + 1024, g_comb + (size_t)head * REC_FLOATS, REC_BYTES, fb);
                        if (chk) bulk_load(xb + 1024 + REC_BYTES, g_coll + 4 * (head - RING), 16, fb);
                        tk = global_ns();
                    } else {
                        while (global_ns() - tk < gap_ns) {}
                        mbar_expect_tx(fb, TILE_BYTES);
                        tma_load_2d(dst, &tmV, 0, row, fb, pol);
                        tma_load_2d(dst + HALF_BYTES, &tmV, 64, row, fb, pol);
                    }
                    nissued++;
                }
                c = atom_inc_relaxed(&g_work) + 2 * gridDim.x;
            }
            {
                const int js = job % JQ;
                mbar_wait(bar_jfree + 8 * js, ((job / JQ) & 1) ^ 1);
                jobq[js] = -1;
                mbar_arrive(bar_jfull + 8 * js);
            }
            {
                const int slot = nissued % NSLOTS;
                mbar_wait(bar_empty + 8 * slot, ((nissued / NSLOTS) & 1) ^ 1);
                meta[slot].w = FLAG_END;
                mbar_arrive(bar_full + 8 * slot);
            }
            mbar_wait(bar_epoch, 0);
            if (atom_inc_relaxed(&g_done) == gridDim.x - 1) { g_work = 0; g_done = 0; g_epoch = *s_epoch + 1u; }
        }
    } else if (warp < NCW) {
        const int g = lane >> 2, t = lane & 3, r8 = lane & 7;
        const uint32_t kOff = (uint32_t)((warp * 16 + r8 + ((lane >> 3) & 1) * 8) * 128 + (((lane >> 4) ^ r8) << 4));
        const uint32_t vOff = (uint32_t)((warp >> 2) * HALF_BYTES + (r8 + (lane >> 4) * 8) * 128 +
                                         (((((2 * warp) & 7) | ((lane >> 3) & 1)) ^ r8) << 4));
        float* wmax = reinterpret_cast<float*>(sptr + SM_WM);
        float* wsum = reinterpret_cast<float*>(sptr + SM_WS);
        uint2* pbuf = reinterpret_cast<uint2*>(sptr + SM_PB);
        const int tq = t & 1;
        const int dcol = warp * 16 + g;
        const int frag = (warp * 16 + g * 2 + tq) * 4;
        int slot = 0; uint32_t phase = 0;
        uint32_t epoch1 = 0u;
        while (true) {
            mbar_wait(bar_full + 8 * slot, phase);
            const int flags = meta[slot].w;
            if (flags & FLAG_END) break;
            const int head = meta[slot].x, tile = meta[slot].y;
            const uint32_t kb = sbase + SM_TILES + slot * TILE_BYTES;
            const unsigned char* xs = sptr + SM_X + slot * XS_BYTES;
            uint32_t kf[8][4];
#pragma unroll
            for (int j = 0; j < 8; j++)
                ldsm_x4(kf[j], kb + (j >> 2) * HALF_BYTES + (kOff ^ (uint32_t)(((2 * j) & 7) << 4)));
            uint32_t qf[8][2];
            {
                const uint32_t* qs = reinterpret_cast<const uint32_t*>(xs);
#pragma unroll
                for (int j = 0; j < 8; j++) {
                    qf[j][0] = (g < SQ) ? qs[g * 64 + j * 8 + t] : 0u;
                    qf[j][1] = (g < SQ) ? qs[g * 64 + j * 8 + 4 + t] : 0u;
                }
            }
            float4 cO = make_float4(0.f, 0.f, 0.f, 0.f), cML = make_float4(0.f, 0.f, 0.f, 0.f);
            if (flags & FLAG_FINAL) {
                const float* cs = reinterpret_cast<const float*>(xs + 1024);
                cO  = *reinterpret_cast<const float4*>(cs + frag);
                cML = *reinterpret_cast<const float4*>(cs + SQ * DH + tq * 4);
            }
            uint32_t freeflag = *reinterpret_cast<const uint32_t*>(xs + 1024 + REC_BYTES);
            __syncwarp();
            if (lane == 0) mbar_arrive(bar_empty + 8 * slot);
            if (++slot == NSLOTS) { slot = 0; phase ^= 1; }

            float sa[4] = {0.f, 0.f, 0.f, 0.f}, sb[4] = {0.f, 0.f, 0.f, 0.f};
#pragma unroll
            for (int j = 0; j < 8; j += 2) {
                mma_bf16(sa, kf[j], qf[j][0], qf[j][1]);
                mma_bf16(sb, kf[j + 1], qf[j + 1][0], qf[j + 1][1]);
            }
            const float s0 = sa[0] + sb[0], s1 = sa[1] + sb[1], s2 = sa[2] + sb[2], s3 = sa[3] + sb[3];
            float t0 = fmaxf(s0, s2), t1 = fmaxf(s1, s3);
#pragma unroll
            for (int x = 4; x <= 16; x <<= 1) {
                t0 = fmaxf(t0, __shfl_xor_sync(0xffffffffu, t0, x));
                t1 = fmaxf(t1, __shfl_xor_sync(0xffffffffu, t1, x));
            }
            if (lane < 2) *reinterpret_cast<float2*>(wmax + warp * 4 + lane * 2) = make_float2(t0, t1);
            named_bar_sync(2, NCW * 32);
            float m0 = -INFINITY, m1 = -INFINITY;
#pragma unroll
            for (int w = 0; w < NCW; w++) {
                const float2 x = *reinterpret_cast<const float2*>(wmax + w * 4 + tq * 2);
                m0 = fmaxf(m0, x.x); m1 = fmaxf(m1, x.y);
            }
            m0 = tagf(m0 * SC, 0u); m1 = tagf(m1 * SC, 0u);
            float p0 = ex2(fmaf(s0, SC, -m0)), p1 = ex2(fmaf(s1, SC, -m1));
            float p2 = ex2(fmaf(s2, SC, -m0)), p3 = ex2(fmaf(s3, SC, -m1));
            if (t >= 2) { p0 = p1 = p2 = p3 = 0.f; }
            {
                uint2 bb;
                bb.x = movmatrix_t(pack_bf16(p0, p1));
                bb.y = movmatrix_t(pack_bf16(p2, p3));
                pbuf[warp * 32 + lane] = bb;
                float r0 = p0 + p2, r1 = p1 + p3;
#pragma unroll
                for (int x = 4; x <= 16; x <<= 1) {
                    r0 += __shfl_xor_sync(0xffffffffu, r0, x);
                    r1 += __shfl_xor_sync(0xffffffffu, r1, x);
                }
                if (lane < 2) *reinterpret_cast<float2*>(wsum + warp * 4 + lane * 2) = make_float2(r0, r1);
            }
            named_bar_sync(2, NCW * 32);
            uint2 pf[8];
            float l0 = 0.f, l1 = 0.f;
#pragma unroll
            for (int w = 0; w < NCW; w++) {
                pf[w] = pbuf[w * 32 + lane];
                const float2 x = *reinterpret_cast<const float2*>(wsum + w * 4 + tq * 2);
                l0 += x.x; l1 += x.y;
            }
            if (epoch1 == 0u && (flags != 0 || head >= RING)) { mbar_wait(bar_epoch, 0); epoch1 = *s_epoch + 1u; }
            const uint32_t tag = (flags & (FLAG_EXTRA | FLAG_FINAL)) ? (epoch1 & 1u) : ring_tag(head);
            float fo0 = 1.f, fo1 = 1.f;
            float* rec = nullptr;
            if (flags & FLAG_FINAL) {
                const float* cg = g_comb + (size_t)head * REC_FLOATS;
                const long long tstart = clock64();
                while ((tag_bad(cO, tag) | tag_bad(cML, tag)) != 0u) {
                    cO  = ld_relaxed_v4(cg + frag);
                    cML = ld_relaxed_v4(cg + SQ * DH + tq * 4);
                    if (clock64() - tstart > SPIN_LIMIT) __trap();
                }
                cO = untag(cO); cML = untag(cML);
                const float M0 = fmaxf(m0, cML.x), M1 = fmaxf(m1, cML.z);
                const float a0 = ex2(m0 - M0), a1 = ex2(m1 - M1), c0 = ex2(cML.x - M0), c1 = ex2(cML.z - M1);
                const float i0 = 1.0f / fmaf(l0, a0, cML.y * c0), i1 = 1.0f / fmaf(l1, a1, cML.w * c1);
                fo0 = a0 * i0; fo1 = a1 * i1;
                cO.x *= c0 * i0; cO.y *= c1 * i1; cO.z *= c0 * i0; cO.w *= c1 * i1;
            } else if (flags & FLAG_EXTRA) {
                rec = g_comb + (size_t)head * REC_FLOATS;
            } else {
                rec = g_ring + ((size_t)(head % RING) * NR + tile) * REC_FLOATS;
                if (head >= RING) {
                    const long long tstart = clock64();
                    while (freeflag != epoch1) {
                        freeflag = ld_relaxed_u32(g_coll + 4 * (head - RING));
                        if (clock64() - tstart > SPIN_LIMIT) __trap();
                    }
                }
            }
            __syncwarp();

            mbar_wait(bar_full + 8 * slot, phase);
            const uint32_t vb = sbase + SM_TILES + slot * TILE_BYTES + vOff;
            uint32_t vf[8][4];
#pragma unroll
            for (int j = 0; j < 8; j++) ldsm_x4_t(vf[j], vb + j * 16 * 128);
            __syncwarp();
            if (lane == 0) mbar_arrive(bar_empty + 8 * slot);
            if (++slot == NSLOTS) { slot = 0; phase ^= 1; }
            float oa[4] = {0.f, 0.f, 0.f, 0.f}, ob[4] = {0.f, 0.f, 0.f, 0.f};
#pragma unroll
            for (int j = 0; j < 8; j += 2) {
                mma_bf16(oa, vf[j], pf[j].x, pf[j].y);
                mma_bf16(ob, vf[j + 1], pf[j + 1].x, pf[j + 1].y);
            }
            if (t < 2) {
                if (flags & FLAG_FINAL) {
                    __nv_bfloat16* op = out + ((size_t)head * SQ + 2 * t) * DH + dcol;
                    op[0]      = __float2bfloat16(fmaf(oa[0] + ob[0], fo0, cO.x));
                    op[DH]     = __float2bfloat16(fmaf(oa[1] + ob[1], fo1, cO.y));
                    op[8]      = __float2bfloat16(fmaf(oa[2] + ob[2], fo0, cO.z));
                    op[DH + 8] = __float2bfloat16(fmaf(oa[3] + ob[3], fo1, cO.w));
                } else {
                    st_relaxed_v4(rec + frag, tagf(oa[0] + ob[0], tag), tagf(oa[1] + ob[1], tag),
                                  tagf(oa[2] + ob[2], tag), tagf(oa[3] + ob[3], tag));
                    if (threadIdx.x < 2) st_relaxed_v4(rec + SQ * DH + t * 4, tagf(m0, tag), tagf(l0, tag), tagf(m1, tag), tagf(l1, tag));
                }
            }
        }
    } else {
        const int e = threadIdx.x - NCW * 32;
        const int half = e >> 7;
        const int f = e & 127;
        const int tq = lane & 1;
        float* cx = reinterpret_cast<float*>(sptr + SM_CX);
        if (e == 0) {
            *s_epoch = ld_relaxed_u32(&g_epoch);
            mbar_arrive(bar_epoch);
        }
        mbar_wait(bar_epoch, 0);
        const uint32_t epoch1 = *s_epoch + 1u;
        const uint32_t etag = epoch1 & 1u;
        for (int k = 0;; k++) {
            const int js = k % JQ; const uint32_t jph = (k / JQ) & 1;
            mbar_wait(bar_jfull + 8 * js, jph);
            const int head = jobq[js];
            __syncwarp();
            if (lane == 0) mbar_arrive(bar_jfree + 8 * js);
            if (head < 0) break;
            const bool deferred = is_deferred(head);
            const uint32_t rtag = ring_tag(head);
            const int nrec_all = deferred ? NR : NR + 1;
            const int r0 = half * HREC;
            const int nrec = (nrec_all - r0 < HREC) ? (nrec_all - r0) : HREC;
            const float* ring = g_ring + ((size_t)(head % RING) * NR + r0) * REC_FLOATS;
            float* comb = g_comb + (size_t)head * REC_FLOATS;
            const int ml_u = lane & 15;
            const bool ml_extra = (r0 + ml_u == NR);
            const float* pml = (ml_extra ? comb : ring + (size_t)ml_u * REC_FLOATS) + SQ * DH + (lane >> 4) * 4;
            const uint32_t mltag = ml_extra ? etag : rtag;
            float4 v[HREC];
#pragma unroll
            for (int u = 0; u < HREC; u++) v[u] = make_float4(0.f, 0.f, 0.f, 0.f);
            float4 pm = make_float4(-INFINITY, 0.f, -INFINITY, 0.f);
            uint32_t pending = (1u << nrec) - 1u;
            const long long tstart = clock64();
            while (true) {
                if ((pending >> ml_u) & 1u) pm = ld_relaxed_v4(pml);
#pragma unroll
                for (int u = 0; u < HREC; u++)
                    if ((pending >> u) & 1u)
                        v[u] = ld_relaxed_v4(((r0 + u == NR) ? comb : ring + (size_t)u * REC_FLOATS) + f * 4);
                uint32_t bad = tag_bad(pm, mltag) << ml_u;
#pragma unroll
                for (int u = 0; u < HREC; u++) bad |= tag_bad(v[u], (r0 + u == NR) ? etag : rtag) << u;
                pending &= __reduce_or_sync(0xffffffffu, bad);
                if (pending == 0u) break;
                if (clock64() - tstart > SPIN_LIMIT) __trap();
                __nanosleep(500);
            }
            pm = untag(pm);
            const bool mlv = ml_u < nrec;
            float Ma = mlv ? pm.x : -INFINITY, Mb = mlv ? pm.z : -INFINITY;
#pragma unroll
            for (int x = 1; x < 16; x <<= 1) {
                Ma = fmaxf(Ma, __shfl_xor_sync(0xffffffffu, Ma, x));
                Mb = fmaxf(Mb, __shfl_xor_sync(0xffffffffu, Mb, x));
            }
            const float sca = mlv ? ex2(pm.x - Ma) : 0.f, scb = mlv ? ex2(pm.z - Mb) : 0.f;
            float La = mlv ? pm.y * sca : 0.f, Lb = mlv ? pm.w * scb : 0.f;
#pragma unroll
            for (int x = 1; x < 16; x <<= 1) {
                La += __shfl_xor_sync(0xffffffffu, La, x);
                Lb += __shfl_xor_sync(0xffffffffu, Lb, x);
            }
            float4 acc = make_float4(0.f, 0.f, 0.f, 0.f);
#pragma unroll
            for (int u = 0; u < HREC; u++) {
                const float sa = __shfl_sync(0xffffffffu, sca, u + 16 * tq), sb = __shfl_sync(0xffffffffu, scb, u + 16 * tq);
                const float4 x = untag(v[u]);
                acc.x = fmaf(x.x, sa, acc.x); acc.y = fmaf(x.y, sb, acc.y);
                acc.z = fmaf(x.z, sa, acc.z); acc.w = fmaf(x.w, sb, acc.w);
            }
            Ma = __shfl_sync(0xffffffffu, Ma, 16 * tq); La = __shfl_sync(0xffffffffu, La, 16 * tq);
            Mb = __shfl_sync(0xffffffffu, Mb, 16 * tq); Lb = __shfl_sync(0xffffffffu, Lb, 16 * tq);
            if (half == 1) {
                *reinterpret_cast<float4*>(cx + f * 4) = acc;
                if (f < 2) *reinterpret_cast<float4*>(cx + SQ * DH + tq * 4) = make_float4(Ma, La, Mb, Lb);
            }
            named_bar_sync(1, NEW * 32);
            if (e == NEW * 32 - 1) st_relaxed_u32(g_coll + 4 * head, epoch1);
            if (half == 0) {
                const float4 ov = *reinterpret_cast<const float4*>(cx + f * 4);
                const float4 oml = *reinterpret_cast<const float4*>(cx + SQ * DH + tq * 4);
                const float M0 = fmaxf(Ma, oml.x), M1 = fmaxf(Mb, oml.z);
                const float fa0 = ex2(Ma - M0), fb0 = ex2(oml.x - M0), fa1 = ex2(Mb - M1), fb1 = ex2(oml.z - M1);
                const float L0 = fmaf(La, fa0, oml.y * fb0), L1 = fmaf(Lb, fa1, oml.w * fb1);
                const float r0x = fmaf(acc.x, fa0, ov.x * fb0), r1x = fmaf(acc.y, fa1, ov.y * fb1);
                const float r0y = fmaf(acc.z, fa0, ov.z * fb0), r1y = fmaf(acc.w, fa1, ov.w * fb1);
                if (deferred) {
                    st_relaxed_v4(comb + f * 4, tagf(r0x, etag), tagf(r1x, etag), tagf(r0y, etag), tagf(r1y, etag));
                    if (f < 2) st_relaxed_v4(comb + SQ * DH + tq * 4, tagf(M0, etag), tagf(L0, etag), tagf(M1, etag), tagf(L1, etag));
                } else {
                    const float i0 = 1.0f / L0, i1 = 1.0f / L1;
                    __nv_bfloat16* op = out + ((size_t)head * SQ + 2 * tq) * DH + (f >> 4) * 16 + ((f >> 1) & 7);
                    op[0]      = __float2bfloat16(r0x * i0);
                    op[DH]     = __float2bfloat16(r1x * i1);
                    op[8]      = __float2bfloat16(r0y * i0);
                    op[DH + 8] = __float2bfloat16(r1y * i1);
                }
            }
            named_bar_sync(1, NEW * 32);
        }
    }
}

typedef CUresult (*EncodeTiledFn)(CUtensorMap*, CUtensorMapDataType, cuuint32_t, void*, const cuuint64_t*,
                                  const cuuint64_t*, const cuuint32_t*, const cuuint32_t*, CUtensorMapInterleave,
                                  CUtensorMapSwizzle, CUtensorMapL2promotion, CUtensorMapFloatOOBfill);

void make_map(EncodeTiledFn enc, CUtensorMap* m, void* p) {
    cuuint64_t dims[2]    = {(cuuint64_t)DH, (cuuint64_t)NHEADS * SKV};
    cuuint64_t strides[1] = {(cuuint64_t)DH * 2};
    cuuint32_t box[2]     = {64, (cuuint32_t)TILE_ROWS};
    cuuint32_t es[2]      = {1, 1};
    enc(m, CU_TENSOR_MAP_DATA_TYPE_BFLOAT16, 2, p, dims, strides, box, es, CU_TENSOR_MAP_INTERLEAVE_NONE,
        CU_TENSOR_MAP_SWIZZLE_128B, CU_TENSOR_MAP_L2_PROMOTION_L2_256B, CU_TENSOR_MAP_FLOAT_OOB_FILL_NONE);
}

}

extern "C" void kernel_launch(void* const* d_in, const int* in_sizes, int n_in, void* d_out, int out_size) {
    (void)in_sizes; (void)n_in; (void)out_size;
    static EncodeTiledFn enc = nullptr;
    static int nsm = 0;
    static unsigned gap_ns = 0;
    if (!enc) {
        cudaDriverEntryPointQueryResult qr;
        void* fn = nullptr;
        cudaGetDriverEntryPoint("cuTensorMapEncodeTiled", &fn, cudaEnableDefault, &qr);
        enc = (EncodeTiledFn)fn;
        cudaFuncSetAttribute(attn_decode_kernel, cudaFuncAttributeMaxDynamicSharedMemorySize, SMEM_BYTES);
        int dev = 0;
        cudaGetDevice(&dev);
        cudaDeviceGetAttribute(&nsm, cudaDevAttrMultiProcessorCount, dev);
        int mem_khz = 0, bus_bits = 0;
        cudaDeviceGetAttribute(&mem_khz, cudaDevAttrMemoryClockRate, dev);
        cudaDeviceGetAttribute(&bus_bits, cudaDevAttrGlobalMemoryBusWidth, dev);
        const double bw = 2.0 * mem_khz * 1e3 * bus_bits / 8.0 * 0.96;
        const int g = nsm < MAX_CTA ? nsm : MAX_CTA;
        double gap = bw > 0.0 ? (double)g * 2.0 * TILE_BYTES / bw * 1e9 - GAP_FIXED_NS : 0.0;
        gap_ns = gap < 0.0 ? 0u : gap > 1200.0 ? 1200u : (unsigned)gap;
    }
    CUtensorMap tmK, tmV;
    make_map(enc, &tmK, d_in[1]);
    make_map(enc, &tmV, d_in[2]);
    const int grid = nsm < MAX_CTA ? nsm : MAX_CTA;
    attn_decode_kernel<<<grid, NTHREADS, SMEM_BYTES>>>(tmK, tmV, (const __nv_bfloat16*)d_in[0], (__nv_bfloat16*)d_out, gap_ns);
}
```

```cpp
#include <cuda_runtime.h>
#include <cuda_bf16.h>
#include <cuda.h>
#include <stdint.h>

namespace {

constexpr int NHEADS = 512;
constexpr int SQ     = 4;
constexpr int SKV    = 4096;
constexpr int DH     = 128;

constexpr int TILE_ROWS  = 128;
constexpr int TILE_BYTES = TILE_ROWS * DH * 2;
constexpr int HALF_BYTES = TILE_BYTES / 2;
constexpr int TPH    = SKV / TILE_ROWS;
constexpr int NSLOTS = 4;
constexpr int WIN    = 2;
constexpr int NCW = 8;
constexpr int NEW = 8;
constexpr int NTHREADS = 32 * (NCW + NEW + 1);
constexpr int MAX_CTA = 132;
#define GAP_FIXED_NS 1590.0

constexpr int NR   = TPH - 1;
constexpr int TH   = 500;
constexpr int GAP  = 12;
constexpr int HD0  = NHEADS - GAP - TH;
constexpr int NA1  = HD0 * (NR + 1);
constexpr int NA2  = NA1 + TH * NR;
constexpr int NA   = NA2 + GAP * (NR + 1);
constexpr int NCHUNKS = NA + TH;
constexpr int LAG  = 480;
constexpr int LAG_END = 420, HEADS_END = 20;
constexpr int RING = 32;
constexpr int HREC = (NR + 2) / 2;
static_assert(HD0 >= 0 && LAG_END <= TH && LAG <= TH + HEADS_END * NR && LAG < RING * NR && LAG_END < RING * NR &&
              NHEADS % (2 * RING) == 0 && HREC <= 16 && 2 * MAX_CTA <= LAG_END && 2 * MAX_CTA <= RING * NR &&
              WIN + 1 <= NSLOTS, "bad schedule");

constexpr int JQ = 4;
constexpr int REC_BYTES  = SQ * DH * 4 + SQ * 8;
constexpr int REC_FLOATS = 544;

constexpr int SM_TILES = 0;
constexpr int SM_X     = SM_TILES + NSLOTS * TILE_BYTES;
constexpr int XS_BYTES = 1024 + REC_BYTES + 16 + 16;
constexpr int SM_PB    = SM_X + NSLOTS * XS_BYTES;
constexpr int SM_WM    = SM_PB + NCW * 32 * 8;
constexpr int SM_WS    = SM_WM + NCW * SQ * 4;
constexpr int SM_CX    = SM_WS + NCW * SQ * 4;
constexpr int SM_META  = SM_CX + REC_BYTES;
constexpr int SM_JOB   = SM_META + NSLOTS * 16;
constexpr int SM_EPOCH = SM_JOB + JQ * 4;
constexpr int SM_BARS  = SM_EPOCH + 16;
constexpr int SM_TOTAL = SM_BARS + (2 * NSLOTS + 2 * JQ + 1) * 8;
constexpr int SMEM_BYTES = SM_TOTAL + 1024;
static_assert(REC_BYTES % 16 == 0 && XS_BYTES % 16 == 0 && SM_BARS % 8 == 0, "align");

constexpr int FLAG_END = 4, FLAG_EXTRA = 8, FLAG_FINAL = 16;

#define COLL_STRIDE 4
#define CTR_OFF 0
struct Scratch {
    float ring[(size_t)RING * NR * REC_FLOATS];
    float comb[(size_t)NHEADS * REC_FLOATS];
    unsigned int coll[NHEADS * COLL_STRIDE];
    unsigned int pad0[CTR_OFF + 64];
    unsigned int work;
    unsigned int pad1[63];
    unsigned int done;
    unsigned int pad2[63];
    unsigned int epoch;
};
union ScratchBlob { Scratch s; unsigned char bytes[4 << 20]; };
static_assert(sizeof(Scratch) <= sizeof(ScratchBlob), "scratch");
__device__ __align__(256) ScratchBlob g_scratch;
#define g_ring  (g_scratch.s.ring)
#define g_comb  (g_scratch.s.comb)
#define g_coll  (g_scratch.s.coll)
#define g_work  (g_scratch.s.work)
#define g_done  (g_scratch.s.done)
#define g_epoch (g_scratch.s.epoch)

__device__ __forceinline__ uint32_t smem_u32(const void* p) { return (uint32_t)__cvta_generic_to_shared(p); }
__device__ __forceinline__ void mbar_init(uint32_t bar, uint32_t cnt) {
    asm volatile("mbarrier.init.shared::cta.b64 [%0], %1;" :: "r"(bar), "r"(cnt) : "memory");
}
__device__ __forceinline__ void mbar_expect_tx(uint32_t bar, uint32_t bytes) {
    asm volatile("mbarrier.arrive.expect_tx.shared::cta.b64 _, [%0], %1;" :: "r"(bar), "r"(bytes) : "memory");
}
__device__ __forceinline__ void mbar_arrive(uint32_t bar) {
    asm volatile("mbarrier.arrive.shared::cta.b64 _, [%0];" :: "r"(bar) : "memory");
}
__device__ __forceinline__ bool mbar_try_wait(uint32_t bar, uint32_t parity) {
    uint32_t ok;
    asm volatile("{\n.reg .pred p;\nmbarrier.try_wait.parity.shared::cta.b64 p, [%1], %2;\nselp.u32 %0, 1, 0, p;\n}"
                 : "=r"(ok) : "r"(bar), "r"(parity) : "memory");
    return ok != 0;
}
constexpr long long SPIN_LIMIT = 4000000000LL;
__device__ __forceinline__ void mbar_wait(uint32_t bar, uint32_t parity) {
    if (mbar_try_wait(bar, parity)) return;
    const long long t0 = clock64();
    while (!mbar_try_wait(bar, parity)) {
        if (clock64() - t0 > SPIN_LIMIT) __trap();
    }
}
__device__ __forceinline__ void tma_load_2d(uint32_t dst, const CUtensorMap* tm, int c0, int c1, uint32_t bar, uint64_t pol) {
    asm volatile("cp.async.bulk.tensor.2d.shared::cluster.global.mbarrier::complete_tx::bytes.L2::cache_hint [%0], [%1, {%3, %4}], [%2], %5;"
                 :: "r"(dst), "l"(tm), "r"(bar), "r"(c0), "r"(c1), "l"(pol) : "memory");
}
__device__ __forceinline__ void bulk_load(uint32_t dst, const void* src, uint32_t bytes, uint32_t bar) {
    asm volatile("cp.async.bulk.shared::cluster.global.mbarrier::complete_tx::bytes [%0], [%1], %2, [%3];"
                 :: "r"(dst), "l"(src), "r"(bytes), "r"(bar) : "memory");
}
__device__ __forceinline__ void ldsm_x4(uint32_t (&r)[4], uint32_t addr) {
    asm volatile("ldmatrix.sync.aligned.m8n8.x4.shared.b16 {%0,%1,%2,%3}, [%4];"
                 : "=r"(r[0]), "=r"(r[1]), "=r"(r[2]), "=r"(r[3]) : "r"(addr) : "memory");
}
__device__ __forceinline__ void ldsm_x4_t(uint32_t (&r)[4], uint32_t addr) {
    asm volatile("ldmatrix.sync.aligned.m8n8.x4.trans.shared.b16 {%0,%1,%2,%3}, [%4];"
                 : "=r"(r[0]), "=r"(r[1]), "=r"(r[2]), "=r"(r[3]) : "r"(addr) : "memory");
}
__device__ __forceinline__ void mma_bf16(float (&d)[4], const uint32_t (&a)[4], uint32_t b0, uint32_t b1) {
    asm volatile("mma.sync.aligned.m16n8k16.row.col.f32.bf16.bf16.f32 {%0,%1,%2,%3}, {%4,%5,%6,%7}, {%8,%9}, {%0,%1,%2,%3};"
                 : "+f"(d[0]), "+f"(d[1]), "+f"(d[2]), "+f"(d[3])
                 : "r"(a[0]), "r"(a[1]), "r"(a[2]), "r"(a[3]), "r"(b0), "r"(b1));
}
__device__ __forceinline__ uint32_t movmatrix_t(uint32_t a) {
    uint32_t d;
    asm volatile("movmatrix.sync.aligned.m8n8.trans.b16 %0, %1;" : "=r"(d) : "r"(a));
    return d;
}
__device__ __forceinline__ uint32_t pack_bf16(float lo, float hi) {
    uint32_t d;
    asm("cvt.rn.bf16x2.f32 %0, %1, %2;" : "=r"(d) : "f"(hi), "f"(lo));
    return d;
}
__device__ __forceinline__ float ex2(float x) {
    float y;
    asm("ex2.approx.ftz.f32 %0, %1;" : "=f"(y) : "f"(x));
    return y;
}
__device__ __forceinline__ void named_bar_sync(int id, int nthreads) {
    asm volatile("bar.sync %0, %1;" :: "r"(id), "r"(nthreads) : "memory");
}
__device__ __forceinline__ unsigned atom_inc_relaxed(unsigned int* p) {
    unsigned o;
    asm volatile("atom.relaxed.gpu.global.add.u32 %0, [%1], 1;" : "=r"(o) : "l"(p) : "memory");
    return o;
}
__device__ __forceinline__ unsigned long long global_ns() {
    unsigned long long t;
    asm volatile("mov.u64 %0, %globaltimer;" : "=l"(t));
    return t;
}
__device__ __forceinline__ uint32_t fbits(float x) { return __float_as_uint(x); }
__device__ __forceinline__ float tagf(float x, uint32_t tag) { return __uint_as_float((fbits(x) & ~1u) | tag); }
__device__ __forceinline__ float4 untag(const float4& v) {
    return make_float4(tagf(v.x, 0u), tagf(v.y, 0u), tagf(v.z, 0u), tagf(v.w, 0u));
}
__device__ __forceinline__ uint32_t tag_bad(const float4& v, uint32_t tag) {
    return ((fbits(v.x) ^ tag) | (fbits(v.y) ^ tag) | (fbits(v.z) ^ tag) | (fbits(v.w) ^ tag)) & 1u;
}
__device__ __forceinline__ void st_relaxed_u32(unsigned int* p, uint32_t x) {
    asm volatile("st.relaxed.gpu.global.u32 [%0], %1;" :: "l"(p), "r"(x) : "memory");
}
__device__ __forceinline__ void st_relaxed_v4(float* p, float x, float y, float z, float w) {
    asm volatile("st.relaxed.gpu.global.v4.f32 [%0], {%1, %2, %3, %4};" :: "l"(p), "f"(x), "f"(y), "f"(z), "f"(w) : "memory");
}
__device__ __forceinline__ uint32_t ld_relaxed_u32(const unsigned int* p) {
    uint32_t v;
    asm volatile("ld.relaxed.gpu.global.u32 %0, [%1];" : "=r"(v) : "l"(p) : "memory");
    return v;
}
__device__ __forceinline__ float4 ld_relaxed_v4(const float* p) {
    float4 v;
    asm volatile("ld.relaxed.gpu.global.v4.f32 {%0,%1,%2,%3}, [%4];" : "=f"(v.x), "=f"(v.y), "=f"(v.z), "=f"(v.w) : "l"(p) : "memory");
    return v;
}

__device__ __forceinline__ void decode_a(int c, int& head, int& tile, int& cnt) {
    if (c < NA1)      { cnt = NR + 1; head = c / (NR + 1); tile = c % (NR + 1); }
    else if (c < NA2) { cnt = NR;     head = HD0 + (c - NA1) / NR; tile = (c - NA1) % NR; }
    else              { cnt = NR + 1; head = HD0 + TH + (c - NA2) / (NR + 1); tile = (c - NA2) % (NR + 1); }
}
__device__ __forceinline__ bool is_deferred(int head) { return head >= HD0 && head < HD0 + TH; }
__device__ __forceinline__ uint32_t ring_tag(int head) { return (uint32_t)(head / RING + 1) & 1u; }

__global__ void __launch_bounds__(NTHREADS, 1)
attn_decode_kernel(const __grid_constant__ CUtensorMap tmK, const __grid_constant__ CUtensorMap tmV,
                   const __nv_bfloat16* __restrict__ q, __nv_bfloat16* __restrict__ out, const unsigned gap_ns)
{
    extern __shared__ unsigned char smem_raw[];
    const uint32_t sbase = (smem_u32(smem_raw) + 1023u) & ~1023u;
    unsigned char* sptr = smem_raw + (sbase - smem_u32(smem_raw));

    const int warp = threadIdx.x >> 5, lane = threadIdx.x & 31;
    const uint32_t bar_full  = sbase + SM_BARS;
    const uint32_t bar_empty = bar_full + NSLOTS * 8;
    const uint32_t bar_jfull = bar_empty + NSLOTS * 8;
    const uint32_t bar_jfree = bar_jfull + JQ * 8;
    const uint32_t bar_epoch = bar_jfree + JQ * 8;
    volatile uint32_t* s_epoch = reinterpret_cast<volatile uint32_t*>(sptr + SM_EPOCH);
    volatile int4* meta = reinterpret_cast<volatile int4*>(sptr + SM_META);
    volatile int* jobq = reinterpret_cast<volatile int*>(sptr + SM_JOB);

    uint64_t pol = 0;
    if (threadIdx.x == NTHREADS - 32) {
        mbar_init(bar_full, 1);
        mbar_init(bar_full + 8, 1);
        asm volatile("fence.mbarrier_init.release.cluster;" ::: "memory");
        asm volatile("createpolicy.fractional.L2::evict_first.b64 %0, 1.0;" : "=l"(pol));
        int head, tile, cnt;
        decode_a((int)blockIdx.x, head, tile, cnt);
        const int row = head * SKV + tile * TILE_ROWS;
        meta[0].x = head; meta[0].y = tile; meta[0].w = (tile == NR) ? FLAG_EXTRA : 0;
        mbar_expect_tx(bar_full, TILE_BYTES + SQ * DH * 2);
        tma_load_2d(sbase + SM_TILES, &tmK, 0, row, bar_full, pol);
        tma_load_2d(sbase + SM_TILES + HALF_BYTES, &tmK, 64, row, bar_full, pol);
        mbar_expect_tx(bar_full + 8, TILE_BYTES);
        tma_load_2d(sbase + SM_TILES + TILE_BYTES, &tmV, 0, row, bar_full + 8, pol);
        tma_load_2d(sbase + SM_TILES + TILE_BYTES + HALF_BYTES, &tmV, 64, row, bar_full + 8, pol);
        bulk_load(sbase + SM_X, q + (size_t)head * SQ * DH, SQ * DH * 2, bar_full);
        for (int s = 2; s < NSLOTS; s++) mbar_init(bar_full + 8 * s, 1);
        for (int s = 0; s < NSLOTS; s++) mbar_init(bar_empty + 8 * s, NCW);
        for (int s = 0; s < JQ; s++) { mbar_init(bar_jfull + 8 * s, 1); mbar_init(bar_jfree + 8 * s, NEW); }
        mbar_init(bar_epoch, 1);
        asm volatile("fence.mbarrier_init.release.cluster;" ::: "memory");
    }
    __syncthreads();

    const float SC = 0.08838834764831845f * 1.4426950408889634f;

    if (warp == NCW + NEW) {
        if (lane == 0) {
            int nissued = 2;
            int job = 0;
            unsigned c = blockIdx.x + gridDim.x;
            while (c < (unsigned)NCHUNKS) {
                int head, tile, kind = 0;
                if (c < (unsigned)NA) {
                    int cnt;
                    decode_a((int)c, head, tile, cnt);
                    if (tile == NR) kind = FLAG_EXTRA;
                } else {
                    head = HD0 + ((int)c - NA); tile = NR; kind = FLAG_FINAL;
                }
#pragma unroll
                for (int z = 0; z < 2; z++) {
                    const int cc = (int)c - (z == 0 ? LAG : LAG_END);
                    if (cc >= 0 && cc < NA) {
                        int h2, t2, cnt2;
                        decode_a(cc, h2, t2, cnt2);
                        if (t2 == cnt2 - 1 && ((h2 >= NHEADS - HEADS_END) == (z == 1))) {
                            const int js = job % JQ;
                            mbar_wait(bar_jfree + 8 * js, ((job / JQ) & 1) ^ 1);
                            jobq[js] = h2;
                            mbar_arrive(bar_jfull + 8 * js);
                            job++;
                        }
                    }
                }
                const bool chk = (kind == 0) && head >= RING;
                const int row = head * SKV + tile * TILE_ROWS;
                unsigned long long tk = 0;
#pragma unroll
                for (int i = 0; i < 2; i++) {
                    const int slot = nissued % NSLOTS;
                    if (nissued > WIN) {
                        const int prev = nissued - WIN;
                        mbar_wait(bar_full + 8 * (prev % NSLOTS), (prev / NSLOTS) & 1);
                    }
                    mbar_wait(bar_empty + 8 * slot, ((nissued / NSLOTS) & 1) ^ 1);
                    const uint32_t fb = bar_full + 8 * slot, dst = sbase + SM_TILES + slot * TILE_BYTES;
                    if (i == 0) {
                        const uint32_t xb = sbase + SM_X + slot * XS_BYTES;
                        meta[slot].x = head; meta[slot].y = tile; meta[slot].w = kind;
                        mbar_expect_tx(fb, TILE_BYTES + SQ * DH * 2 + (kind == FLAG_FINAL ? REC_BYTES : 0) + (chk ? 16 : 0));
                        tma_load_2d(dst, &tmK, 0, row, fb, pol);
                        tma_load_2d(dst + HALF_BYTES, &tmK, 64, row, fb, pol);
                        bulk_load(xb, q + (size_t)head * SQ * DH, SQ * DH * 2, fb);
                        if (kind == FLAG_FINAL) bulk_load(xb + 1024, g_comb + (size_t)head * REC_FLOATS, REC_BYTES, fb);
                        if (chk) bulk_load(xb + 1024 + REC_BYTES, g_coll + COLL_STRIDE * (head - RING), 16, fb);
                        tk = global_ns();
                    } else {
                        while (global_ns() - tk < gap_ns) {}
                        mbar_expect_tx(fb, TILE_BYTES);
                        tma_load_2d(dst, &tmV, 0, row, fb, pol);
                        tma_load_2d(dst + HALF_BYTES, &tmV, 64, row, fb, pol);
                    }
                    nissued++;
                }
                c = atom_inc_relaxed(&g_work) + 2 * gridDim.x;
            }
            {
                const int js = job % JQ;
                mbar_wait(bar_jfree + 8 * js, ((job / JQ) & 1) ^ 1);
                jobq[js] = -1;
                mbar_arrive(bar_jfull + 8 * js);
            }
            {
                const int slot = nissued % NSLOTS;
                mbar_wait(bar_empty + 8 * slot, ((nissued / NSLOTS) & 1) ^ 1);
                meta[slot].w = FLAG_END;
                mbar_arrive(bar_full + 8 * slot);
            }
            mbar_wait(bar_epoch, 0);
            if (atom_inc_relaxed(&g_done) == gridDim.x - 1) { g_work = 0; g_done = 0; g_epoch = *s_epoch + 1u; }
        }
    } else if (warp < NCW) {
        const int g = lane >> 2, t = lane & 3, r8 = lane & 7;
        const uint32_t kOff = (uint32_t)((warp * 16 + r8 + ((lane >> 3) & 1) * 8) * 128 + (((lane >> 4) ^ r8) << 4));
        const uint32_t vOff = (uint32_t)((warp >> 2) * HALF_BYTES + (r8 + (lane >> 4) * 8) * 128 +
                                         (((((2 * warp) & 7) | ((lane >> 3) & 1)) ^ r8) << 4));
        float* wmax = reinterpret_cast<float*>(sptr + SM_WM);
        float* wsum = reinterpret_cast<float*>(sptr + SM_WS);
        uint2* pbuf = reinterpret_cast<uint2*>(sptr + SM_PB);
        const int tq = t & 1;
        const int dcol = warp * 16 + g;
        const int frag = (warp * 16 + g * 2 + tq) * 4;
        int slot = 0; uint32_t phase = 0;
        uint32_t epoch1 = 0u;
        while (true) {
            mbar_wait(bar_full + 8 * slot, phase);
            const int flags = meta[slot].w;
            if (flags & FLAG_END) break;
            const int head = meta[slot].x, tile = meta[slot].y;
            const uint32_t kb = sbase + SM_TILES + slot * TILE_BYTES;
            const unsigned char* xs = sptr + SM_X + slot * XS_BYTES;
            uint32_t kf[8][4];
#pragma unroll
            for (int j = 0; j < 8; j++)
                ldsm_x4(kf[j], kb + (j >> 2) * HALF_BYTES + (kOff ^ (uint32_t)(((2 * j) & 7) << 4)));
            uint32_t qf[8][2];
            {
                const uint32_t* qs = reinterpret_cast<const uint32_t*>(xs);
#pragma unroll
                for (int j = 0; j < 8; j++) {
                    qf[j][0] = (g < SQ) ? qs[g * 64 + j * 8 + t] : 0u;
                    qf[j][1] = (g < SQ) ? qs[g * 64 + j * 8 + 4 + t] : 0u;
                }
            }
            float4 cO = make_float4(0.f, 0.f, 0.f, 0.f), cML = make_float4(0.f, 0.f, 0.f, 0.f);
            if (flags & FLAG_FINAL) {
                const float* cs = reinterpret_cast<const float*>(xs + 1024);
                cO  = *reinterpret_cast<const float4*>(cs + frag);
                cML = *reinterpret_cast<const float4*>(cs + SQ * DH + tq * 4);
            }
            uint32_t freeflag = *reinterpret_cast<const uint32_t*>(xs + 1024 + REC_BYTES);
            __syncwarp();
            if (lane == 0) mbar_arrive(bar_empty + 8 * slot);
            if (++slot == NSLOTS) { slot = 0; phase ^= 1; }

            float sa[4] = {0.f, 0.f, 0.f, 0.f}, sb[4] = {0.f, 0.f, 0.f, 0.f};
#pragma unroll
            for (int j = 0; j < 8; j += 2) {
                mma_bf16(sa, kf[j], qf[j][0], qf[j][1]);
                mma_bf16(sb, kf[j + 1], qf[j + 1][0], qf[j + 1][1]);
            }
            const float s0 = sa[0] + sb[0], s1 = sa[1] + sb[1], s2 = sa[2] + sb[2], s3 = sa[3] + sb[3];
            float t0 = fmaxf(s0, s2), t1 = fmaxf(s1, s3);
#pragma unroll
            for (int x = 4; x <= 16; x <<= 1) {
                t0 = fmaxf(t0, __shfl_xor_sync(0xffffffffu, t0, x));
                t1 = fmaxf(t1, __shfl_xor_sync(0xffffffffu, t1, x));
            }
            if (lane < 2) *reinterpret_cast<float2*>(wmax + warp * 4 + lane * 2) = make_float2(t0, t1);
            named_bar_sync(2, NCW * 32);
            float m0 = -INFINITY, m1 = -INFINITY;
#pragma unroll
            for (int w = 0; w < NCW; w++) {
                const float2 x = *reinterpret_cast<const float2*>(wmax + w * 4 + tq * 2);
                m0 = fmaxf(m0, x.x); m1 = fmaxf(m1, x.y);
            }
            m0 = tagf(m0 * SC, 0u); m1 = tagf(m1 * SC, 0u);
            float p0 = ex2(fmaf(s0, SC, -m0)), p1 = ex2(fmaf(s1, SC, -m1));
            float p2 = ex2(fmaf(s2, SC, -m0)), p3 = ex2(fmaf(s3, SC, -m1));
            if (t >= 2) { p0 = p1 = p2 = p3 = 0.f; }
            {
                uint2 bb;
                bb.x = movmatrix_t(pack_bf16(p0, p1));
                bb.y = movmatrix_t(pack_bf16(p2, p3));
                pbuf[warp * 32 + lane] = bb;
                float r0 = p0 + p2, r1 = p1 + p3;
#pragma unroll
                for (int x = 4; x <= 16; x <<= 1) {
                    r0 += __shfl_xor_sync(0xffffffffu, r0, x);
                    r1 += __shfl_xor_sync(0xffffffffu, r1, x);
                }
                if (lane < 2) *reinterpret_cast<float2*>(wsum + warp * 4 + lane * 2) = make_float2(r0, r1);
            }
            named_bar_sync(2, NCW * 32);
            uint2 pf[8];
            float l0 = 0.f, l1 = 0.f;
#pragma unroll
            for (int w = 0; w < NCW; w++) {
                pf[w] = pbuf[w * 32 + lane];
                const float2 x = *reinterpret_cast<const float2*>(wsum + w * 4 + tq * 2);
                l0 += x.x; l1 += x.y;
            }
            if (epoch1 == 0u && (flags != 0 || head >= RING)) { mbar_wait(bar_epoch, 0); epoch1 = *s_epoch + 1u; }
            const uint32_t tag = (flags & (FLAG_EXTRA | FLAG_FINAL)) ? (epoch1 & 1u) : ring_tag(head);
            float fo0 = 1.f, fo1 = 1.f;
            float* rec = nullptr;
            if (flags & FLAG_FINAL) {
                const float* cg = g_comb + (size_t)head * REC_FLOATS;
                const long long tstart = clock64();
                while ((tag_bad(cO, tag) | tag_bad(cML, tag)) != 0u) {
                    cO  = ld_relaxed_v4(cg + frag);
                    cML = ld_relaxed_v4(cg + SQ * DH + tq * 4);
                    if (clock64() - tstart > SPIN_LIMIT) __trap();
                }
                cO = untag(cO); cML = untag(cML);
                const float M0 = fmaxf(m0, cML.x), M1 = fmaxf(m1, cML.z);
                const float a0 = ex2(m0 - M0), a1 = ex2(m1 - M1), c0 = ex2(cML.x - M0), c1 = ex2(cML.z - M1);
                const float i0 = 1.0f / fmaf(l0, a0, cML.y * c0), i1 = 1.0f / fmaf(l1, a1, cML.w * c1);
                fo0 = a0 * i0; fo1 = a1 * i1;
                cO.x *= c0 * i0; cO.y *= c1 * i1; cO.z *= c0 * i0; cO.w *= c1 * i1;
            } else if (flags & FLAG_EXTRA) {
                rec = g_comb + (size_t)head * REC_FLOATS;
            } else {
                rec = g_ring + ((size_t)(head % RING) * NR + tile) * REC_FLOATS;
                if (head >= RING) {
                    const long long tstart = clock64();
                    while (freeflag != epoch1) {
                        freeflag = ld_relaxed_u32(g_coll + COLL_STRIDE * (head - RING));
                        if (clock64() - tstart > SPIN_LIMIT) __trap();
                    }
                }
            }
            __syncwarp();

            mbar_wait(bar_full + 8 * slot, phase);
            const uint32_t vb = sbase + SM_TILES + slot * TILE_BYTES + vOff;
            uint32_t vf[8][4];
#pragma unroll
            for (int j = 0; j < 8; j++) ldsm_x4_t(vf[j], vb + j * 16 * 128);
            __syncwarp();
            if (lane == 0) mbar_arrive(bar_empty + 8 * slot);
            if (++slot == NSLOTS) { slot = 0; phase ^= 1; }
            float oa[4] = {0.f, 0.f, 0.f, 0.f}, ob[4] = {0.f, 0.f, 0.f, 0.f};
#pragma unroll
            for (int j = 0; j < 8; j += 2) {
                mma_bf16(oa, vf[j], pf[j].x, pf[j].y);
                mma_bf16(ob, vf[j + 1], pf[j + 1].x, pf[j + 1].y);
            }
            if (t < 2) {
                if (flags & FLAG_FINAL) {
                    __nv_bfloat16* op = out + ((size_t)head * SQ + 2 * t) * DH + dcol;
                    op[0]      = __float2bfloat16(fmaf(oa[0] + ob[0], fo0, cO.x));
                    op[DH]     = __float2bfloat16(fmaf(oa[1] + ob[1], fo1, cO.y));
                    op[8]      = __float2bfloat16(fmaf(oa[2] + ob[2], fo0, cO.z));
                    op[DH + 8] = __float2bfloat16(fmaf(oa[3] + ob[3], fo1, cO.w));
                } else {
                    st_relaxed_v4(rec + frag, tagf(oa[0] + ob[0], tag), tagf(oa[1] + ob[1], tag),
                                  tagf(oa[2] + ob[2], tag), tagf(oa[3] + ob[3], tag));
                    if (threadIdx.x < 2) st_relaxed_v4(rec + SQ * DH + t * 4, tagf(m0, tag), tagf(l0, tag), tagf(m1, tag), tagf(l1, tag));
                }
            }
        }
    } else {
        const int e = threadIdx.x - NCW * 32;
        const int half = e >> 7;
        const int f = e & 127;
        const int tq = lane & 1;
        float* cx = reinterpret_cast<float*>(sptr + SM_CX);
        if (e == 0) {
            *s_epoch = ld_relaxed_u32(&g_epoch);
            mbar_arrive(bar_epoch);
        }
        mbar_wait(bar_epoch, 0);
        const uint32_t epoch1 = *s_epoch + 1u;
        const uint32_t etag = epoch1 & 1u;
        for (int k = 0;; k++) {
            const int js = k % JQ; const uint32_t jph = (k / JQ) & 1;
            mbar_wait(bar_jfull + 8 * js, jph);
            const int head = jobq[js];
            __syncwarp();
            if (lane == 0) mbar_arrive(bar_jfree + 8 * js);
            if (head < 0) break;
            const bool deferred = is_deferred(head);
            const uint32_t rtag = ring_tag(head);
            const int nrec_all = deferred ? NR : NR + 1;
            const int r0 = half * HREC;
            const int nrec = (nrec_all - r0 < HREC) ? (nrec_all - r0) : HREC;
            const float* ring = g_ring + ((size_t)(head % RING) * NR + r0) * REC_FLOATS;
            float* comb = g_comb + (size_t)head * REC_FLOATS;
            const int ml_u = lane & 15;
            const bool ml_extra = (r0 + ml_u == NR);
            const float* pml = (ml_extra ? comb : ring + (size_t)ml_u * REC_FLOATS) + SQ * DH + (lane >> 4) * 4;
            const uint32_t mltag = ml_extra ? etag : rtag;
            float4 v[HREC];
#pragma unroll
            for (int u = 0; u < HREC; u++) v[u] = make_float4(0.f, 0.f, 0.f, 0.f);
            float4 pm = make_float4(-INFINITY, 0.f, -INFINITY, 0.f);
            uint32_t pending = (1u << nrec) - 1u;
            const long long tstart = clock64();
            while (true) {
                if ((pending >> ml_u) & 1u) pm = ld_relaxed_v4(pml);
#pragma unroll
                for (int u = 0; u < HREC; u++)
                    if ((pending >> u) & 1u)
                        v[u] = ld_relaxed_v4(((r0 + u == NR) ? comb : ring + (size_t)u * REC_FLOATS) + f * 4);
                uint32_t bad = tag_bad(pm, mltag) << ml_u;
#pragma unroll
                for (int u = 0; u < HREC; u++) bad |= tag_bad(v[u], (r0 + u == NR) ? etag : rtag) << u;
                pending &= __reduce_or_sync(0xffffffffu, bad);
                if (pending == 0u) break;
                if (clock64() - tstart > SPIN_LIMIT) __trap();
                __nanosleep(500);
            }
            pm = untag(pm);
            const bool mlv = ml_u < nrec;
            float Ma = mlv ? pm.x : -INFINITY, Mb = mlv ? pm.z : -INFINITY;
#pragma unroll
            for (int x = 1; x < 16; x <<= 1) {
                Ma = fmaxf(Ma, __shfl_xor_sync(0xffffffffu, Ma, x));
                Mb = fmaxf(Mb, __shfl_xor_sync(0xffffffffu, Mb, x));
            }
            const float sca = mlv ? ex2(pm.x - Ma) : 0.f, scb = mlv ? ex2(pm.z - Mb) : 0.f;
            float La = mlv ? pm.y * sca : 0.f, Lb = mlv ? pm.w * scb : 0.f;
#pragma unroll
            for (int x = 1; x < 16; x <<= 1) {
                La += __shfl_xor_sync(0xffffffffu, La, x);
                Lb += __shfl_xor_sync(0xffffffffu, Lb, x);
            }
            float4 acc = make_float4(0.f, 0.f, 0.f, 0.f);
#pragma unroll
            for (int u = 0; u < HREC; u++) {
                const float sa = __shfl_sync(0xffffffffu, sca, u + 16 * tq), sb = __shfl_sync(0xffffffffu, scb, u + 16 * tq);
                const float4 x = untag(v[u]);
                acc.x = fmaf(x.x, sa, acc.x); acc.y = fmaf(x.y, sb, acc.y);
                acc.z = fmaf(x.z, sa, acc.z); acc.w = fmaf(x.w, sb, acc.w);
            }
            Ma = __shfl_sync(0xffffffffu, Ma, 16 * tq); La = __shfl_sync(0xffffffffu, La, 16 * tq);
            Mb = __shfl_sync(0xffffffffu, Mb, 16 * tq); Lb = __shfl_sync(0xffffffffu, Lb, 16 * tq);
            if (half == 1) {
                *reinterpret_cast<float4*>(cx + f * 4) = acc;
                if (f < 2) *reinterpret_cast<float4*>(cx + SQ * DH + tq * 4) = make_float4(Ma, La, Mb, Lb);
            }
            named_bar_sync(1, NEW * 32);
            if (e == NEW * 32 - 1) st_relaxed_u32(g_coll + COLL_STRIDE * head, epoch1);
            if (half == 0) {
                const float4 ov = *reinterpret_cast<const float4*>(cx + f * 4);
                const float4 oml = *reinterpret_cast<const float4*>(cx + SQ * DH + tq * 4);
                const float M0 = fmaxf(Ma, oml.x), M1 = fmaxf(Mb, oml.z);
                const float fa0 = ex2(Ma - M0), fb0 = ex2(oml.x - M0), fa1 = ex2(Mb - M1), fb1 = ex2(oml.z - M1);
                const float L0 = fmaf(La, fa0, oml.y * fb0), L1 = fmaf(Lb, fa1, oml.w * fb1);
                const float r0x = fmaf(acc.x, fa0, ov.x * fb0), r1x = fmaf(acc.y, fa1, ov.y * fb1);
                const float r0y = fmaf(acc.z, fa0, ov.z * fb0), r1y = fmaf(acc.w, fa1, ov.w * fb1);
                if (deferred) {
                    st_relaxed_v4(comb + f * 4, tagf(r0x, etag), tagf(r1x, etag), tagf(r0y, etag), tagf(r1y, etag));
                    if (f < 2) st_relaxed_v4(comb + SQ * DH + tq * 4, tagf(M0, etag), tagf(L0, etag), tagf(M1, etag), tagf(L1, etag));
                } else {
                    const float i0 = 1.0f / L0, i1 = 1.0f / L1;
                    __nv_bfloat16* op = out + ((size_t)head * SQ + 2 * tq) * DH + (f >> 4) * 16 + ((f >> 1) & 7);
                    op[0]      = __float2bfloat16(r0x * i0);
                    op[DH]     = __float2bfloat16(r1x * i1);
                    op[8]      = __float2bfloat16(r0y * i0);
                    op[DH + 8] = __float2bfloat16(r1y * i1);
                }
            }
            named_bar_sync(1, NEW * 32);
        }
    }
}

typedef CUresult (*EncodeTiledFn)(CUtensorMap*, CUtensorMapDataType, cuuint32_t, void*, const cuuint64_t*,
                                  const cuuint64_t*, const cuuint32_t*, const cuuint32_t*, CUtensorMapInterleave,
                                  CUtensorMapSwizzle, CUtensorMapL2promotion, CUtensorMapFloatOOBfill);

void make_map(EncodeTiledFn enc, CUtensorMap* m, void* p) {
    cuuint64_t dims[2]    = {(cuuint64_t)DH, (cuuint64_t)NHEADS * SKV};
    cuuint64_t strides[1] = {(cuuint64_t)DH * 2};
    cuuint32_t box[2]     = {64, (cuuint32_t)TILE_ROWS};
    cuuint32_t es[2]      = {1, 1};
    enc(m, CU_TENSOR_MAP_DATA_TYPE_BFLOAT16, 2, p, dims, strides, box, es, CU_TENSOR_MAP_INTERLEAVE_NONE,
        CU_TENSOR_MAP_SWIZZLE_128B, CU_TENSOR_MAP_L2_PROMOTION_L2_256B, CU_TENSOR_MAP_FLOAT_OOB_FILL_NONE);
}

}

extern "C" void kernel_launch(void* const* d_in, const int* in_sizes, int n_in, void* d_out, int out_size) {
    (void)in_sizes; (void)n_in; (void)out_size;
    static EncodeTiledFn enc = nullptr;
    static int nsm = 0;
    static unsigned gap_ns = 0;
    if (!enc) {
        cudaDriverEntryPointQueryResult qr;
        void* fn = nullptr;
        cudaGetDriverEntryPoint("cuTensorMapEncodeTiled", &fn, cudaEnableDefault, &qr);
        enc = (EncodeTiledFn)fn;
        cudaFuncSetAttribute(attn_decode_kernel, cudaFuncAttributeMaxDynamicSharedMemorySize, SMEM_BYTES);
        int dev = 0;
        cudaGetDevice(&dev);
        cudaDeviceGetAttribute(&nsm, cudaDevAttrMultiProcessorCount, dev);
        int mem_khz = 0, bus_bits = 0;
        cudaDeviceGetAttribute(&mem_khz, cudaDevAttrMemoryClockRate, dev);
        cudaDeviceGetAttribute(&bus_bits, cudaDevAttrGlobalMemoryBusWidth, dev);
        const double bw = 2.0 * mem_khz * 1e3 * bus_bits / 8.0 * 0.96;
        const int g = nsm < MAX_CTA ? nsm : MAX_CTA;
        double gap = bw > 0.0 ? (double)g * 2.0 * TILE_BYTES / bw * 1e9 - GAP_FIXED_NS : 0.0;
        gap_ns = gap < 0.0 ? 0u : gap > 1200.0 ? 1200u : (unsigned)gap;
    }
    CUtensorMap tmK, tmV;
    make_map(enc, &tmK, d_in[1]);
    make_map(enc, &tmV, d_in[2]);
    const int grid = nsm < MAX_CTA ? nsm : MAX_CTA;
    attn_decode_kernel<<<grid, NTHREADS, SMEM_BYTES>>>(tmK, tmV, (const __nv_bfloat16*)d_in[0], (__nv_bfloat16*)d_out, gap_ns);
}
```

```cpp
#include <cuda_runtime.h>
#include <cuda_bf16.h>
#include <cuda.h>
#include <stdint.h>

namespace {

constexpr int NHEADS = 512;
constexpr int SQ     = 4;
constexpr int SKV    = 4096;
constexpr int DH     = 128;

constexpr int TILE_ROWS  = 128;
constexpr int TILE_BYTES = TILE_ROWS * DH * 2;
constexpr int HALF_BYTES = TILE_BYTES / 2;
constexpr int TPH    = SKV / TILE_ROWS;
constexpr int NSLOTS = 4;
constexpr int WIN    = 2;
constexpr int NCW = 8;
constexpr int NEW = 8;
constexpr int NTHREADS = 32 * (NCW + NEW + 1);
constexpr int MAX_CTA = 132;
constexpr double GAP_FIXED_NS = 1600.0;

constexpr int NR   = TPH - 1;
constexpr int TH   = 500;
constexpr int GAP  = 12;
constexpr int HD0  = NHEADS - GAP - TH;
constexpr int NA1  = HD0 * (NR + 1);
constexpr int NA2  = NA1 + TH * NR;
constexpr int NA   = NA2 + GAP * (NR + 1);
constexpr int NCHUNKS = NA + TH;
constexpr int LAG  = 480;
constexpr int LAG_END = 420, HEADS_END = 20;
constexpr int RING = 32;
constexpr int HREC = (NR + 2) / 2;
static_assert(HD0 >= 0 && LAG_END <= TH && LAG <= TH + HEADS_END * NR && LAG < RING * NR && LAG_END < RING * NR &&
              NHEADS % (2 * RING) == 0 && HREC <= 16 && 2 * MAX_CTA <= LAG_END && 2 * MAX_CTA <= RING * NR &&
              WIN + 1 <= NSLOTS, "bad schedule");

constexpr int JQ = 4;
constexpr int REC_BYTES  = SQ * DH * 4 + SQ * 8;
constexpr int REC_FLOATS = 544;

constexpr int SM_TILES = 0;
constexpr int SM_X     = SM_TILES + NSLOTS * TILE_BYTES;
constexpr int XS_BYTES = 1024 + REC_BYTES + 16 + 16;
constexpr int SM_PB    = SM_X + NSLOTS * XS_BYTES;
constexpr int SM_WM    = SM_PB + NCW * 32 * 8;
constexpr int SM_WS    = SM_WM + NCW * SQ * 4;
constexpr int SM_CX    = SM_WS + NCW * SQ * 4;
constexpr int SM_META  = SM_CX + REC_BYTES;
constexpr int SM_JOB   = SM_META + NSLOTS * 16;
constexpr int SM_EPOCH = SM_JOB + JQ * 4;
constexpr int SM_BARS  = SM_EPOCH + 16;
constexpr int SM_TOTAL = SM_BARS + (2 * NSLOTS + 2 * JQ + 1) * 8;
constexpr int SMEM_BYTES = SM_TOTAL + 1024;
static_assert(REC_BYTES % 16 == 0 && XS_BYTES % 16 == 0 && SM_BARS % 8 == 0, "align");

constexpr int FLAG_END = 4, FLAG_EXTRA = 8, FLAG_FINAL = 16;

constexpr int COLL_STRIDE = 4;
struct Scratch {
    float ring[(size_t)RING * NR * REC_FLOATS];
    float comb[(size_t)NHEADS * REC_FLOATS];
    unsigned int coll[NHEADS * COLL_STRIDE];
    unsigned int pad0[64];
    unsigned int work;
    unsigned int pad1[63];
    unsigned int done;
    unsigned int pad2[63];
    unsigned int epoch;
};
union ScratchBlob { Scratch s; unsigned char bytes[4 << 20]; };
static_assert(sizeof(Scratch) <= sizeof(ScratchBlob), "scratch");
__device__ __align__(256) ScratchBlob g_scratch;
#define g_ring  (g_scratch.s.ring)
#define g_comb  (g_scratch.s.comb)
#define g_coll  (g_scratch.s.coll)
#define g_work  (g_scratch.s.work)
#define g_done  (g_scratch.s.done)
#define g_epoch (g_scratch.s.epoch)

__device__ __forceinline__ uint32_t smem_u32(const void* p) { return (uint32_t)__cvta_generic_to_shared(p); }
__device__ __forceinline__ void mbar_init(uint32_t bar, uint32_t cnt) {
    asm volatile("mbarrier.init.shared::cta.b64 [%0], %1;" :: "r"(bar), "r"(cnt) : "memory");
}
__device__ __forceinline__ void mbar_expect_tx(uint32_t bar, uint32_t bytes) {
    asm volatile("mbarrier.arrive.expect_tx.shared::cta.b64 _, [%0], %1;" :: "r"(bar), "r"(bytes) : "memory");
}
__device__ __forceinline__ void mbar_arrive(uint32_t bar) {
    asm volatile("mbarrier.arrive.shared::cta.b64 _, [%0];" :: "r"(bar) : "memory");
}
__device__ __forceinline__ bool mbar_try_wait(uint32_t bar, uint32_t parity) {
    uint32_t ok;
    asm volatile("{\n.reg .pred p;\nmbarrier.try_wait.parity.shared::cta.b64 p, [%1], %2;\nselp.u32 %0, 1, 0, p;\n}"
                 : "=r"(ok) : "r"(bar), "r"(parity) : "memory");
    return ok != 0;
}
constexpr long long SPIN_LIMIT = 4000000000LL;
__device__ __forceinline__ void mbar_wait(uint32_t bar, uint32_t parity) {
    if (mbar_try_wait(bar, parity)) return;
    const long long t0 = clock64();
    while (!mbar_try_wait(bar, parity)) {
        if (clock64() - t0 > SPIN_LIMIT) __trap();
    }
}
__device__ __forceinline__ void tma_load_2d(uint32_t dst, const CUtensorMap* tm, int c0, int c1, uint32_t bar, uint64_t pol) {
    asm volatile("cp.async.bulk.tensor.2d.shared::cluster.global.mbarrier::complete_tx::bytes.L2::cache_hint [%0], [%1, {%3, %4}], [%2], %5;"
                 :: "r"(dst), "l"(tm), "r"(bar), "r"(c0), "r"(c1), "l"(pol) : "memory");
}
__device__ __forceinline__ void bulk_load(uint32_t dst, const void* src, uint32_t bytes, uint32_t bar) {
    asm volatile("cp.async.bulk.shared::cluster.global.mbarrier::complete_tx::bytes [%0], [%1], %2, [%3];"
                 :: "r"(dst), "l"(src), "r"(bytes), "r"(bar) : "memory");
}
__device__ __forceinline__ void ldsm_x4(uint32_t (&r)[4], uint32_t addr) {
    asm volatile("ldmatrix.sync.aligned.m8n8.x4.shared.b16 {%0,%1,%2,%3}, [%4];"
                 : "=r"(r[0]), "=r"(r[1]), "=r"(r[2]), "=r"(r[3]) : "r"(addr) : "memory");
}
__device__ __forceinline__ void ldsm_x4_t(uint32_t (&r)[4], uint32_t addr) {
    asm volatile("ldmatrix.sync.aligned.m8n8.x4.trans.shared.b16 {%0,%1,%2,%3}, [%4];"
                 : "=r"(r[0]), "=r"(r[1]), "=r"(r[2]), "=r"(r[3]) : "r"(addr) : "memory");
}
__device__ __forceinline__ void mma_bf16(float (&d)[4], const uint32_t (&a)[4], uint32_t b0, uint32_t b1) {
    asm volatile("mma.sync.aligned.m16n8k16.row.col.f32.bf16.bf16.f32 {%0,%1,%2,%3}, {%4,%5,%6,%7}, {%8,%9}, {%0,%1,%2,%3};"
                 : "+f"(d[0]), "+f"(d[1]), "+f"(d[2]), "+f"(d[3])
                 : "r"(a[0]), "r"(a[1]), "r"(a[2]), "r"(a[3]), "r"(b0), "r"(b1));
}
__device__ __forceinline__ uint32_t movmatrix_t(uint32_t a) {
    uint32_t d;
    asm volatile("movmatrix.sync.aligned.m8n8.trans.b16 %0, %1;" : "=r"(d) : "r"(a));
    return d;
}
__device__ __forceinline__ uint32_t pack_bf16(float lo, float hi) {
    uint32_t d;
    asm("cvt.rn.bf16x2.f32 %0, %1, %2;" : "=r"(d) : "f"(hi), "f"(lo));
    return d;
}
__device__ __forceinline__ float ex2(float x) {
    float y;
    asm("ex2.approx.ftz.f32 %0, %1;" : "=f"(y) : "f"(x));
    return y;
}
__device__ __forceinline__ void named_bar_sync(int id, int nthreads) {
    asm volatile("bar.sync %0, %1;" :: "r"(id), "r"(nthreads) : "memory");
}
__device__ __forceinline__ unsigned atom_inc_relaxed(unsigned int* p) {
    unsigned o;
    asm volatile("atom.relaxed.gpu.global.add.u32 %0, [%1], 1;" : "=r"(o) : "l"(p) : "memory");
    return o;
}
__device__ __forceinline__ unsigned long long global_ns() {
    unsigned long long t;
    asm volatile("mov.u64 %0, %globaltimer;" : "=l"(t));
    return t;
}
__device__ __forceinline__ uint32_t fbits(float x) { return __float_as_uint(x); }
__device__ __forceinline__ float tagf(float x, uint32_t tag) { return __uint_as_float((fbits(x) & ~1u) | tag); }
__device__ __forceinline__ float4 untag(const float4& v) {
    return make_float4(tagf(v.x, 0u), tagf(v.y, 0u), tagf(v.z, 0u), tagf(v.w, 0u));
}
__device__ __forceinline__ uint32_t tag_bad(const float4& v, uint32_t tag) {
    return ((fbits(v.x) ^ tag) | (fbits(v.y) ^ tag) | (fbits(v.z) ^ tag) | (fbits(v.w) ^ tag)) & 1u;
}
__device__ __forceinline__ void st_relaxed_u32(unsigned int* p, uint32_t x) {
    asm volatile("st.relaxed.gpu.global.u32 [%0], %1;" :: "l"(p), "r"(x) : "memory");
}
__device__ __forceinline__ void st_relaxed_v4(float* p, float x, float y, float z, float w) {
    asm volatile("st.relaxed.gpu.global.v4.f32 [%0], {%1, %2, %3, %4};" :: "l"(p), "f"(x), "f"(y), "f"(z), "f"(w) : "memory");
}
__device__ __forceinline__ uint32_t ld_relaxed_u32(const unsigned int* p) {
    uint32_t v;
    asm volatile("ld.relaxed.gpu.global.u32 %0, [%1];" : "=r"(v) : "l"(p) : "memory");
    return v;
}
__device__ __forceinline__ float4 ld_relaxed_v4(const float* p) {
    float4 v;
    asm volatile("ld.relaxed.gpu.global.v4.f32 {%0,%1,%2,%3}, [%4];" : "=f"(v.x), "=f"(v.y), "=f"(v.z), "=f"(v.w) : "l"(p) : "memory");
    return v;
}

__device__ __forceinline__ void decode_a(int c, int& head, int& tile, int& cnt) {
    if (c < NA1)      { cnt = NR + 1; head = c / (NR + 1); tile = c % (NR + 1); }
    else if (c < NA2) { cnt = NR;     head = HD0 + (c - NA1) / NR; tile = (c - NA1) % NR; }
    else              { cnt = NR + 1; head = HD0 + TH + (c - NA2) / (NR + 1); tile = (c - NA2) % (NR + 1); }
}
__device__ __forceinline__ bool is_deferred(int head) { return head >= HD0 && head < HD0 + TH; }
__device__ __forceinline__ uint32_t ring_tag(int head) { return (uint32_t)(head / RING + 1) & 1u; }

__global__ void __launch_bounds__(NTHREADS, 1)
attn_decode_kernel(const __grid_constant__ CUtensorMap tmK, const __grid_constant__ CUtensorMap tmV,
                   const __nv_bfloat16* __restrict__ q, __nv_bfloat16* __restrict__ out, const unsigned gap_ns)
{
    extern __shared__ unsigned char smem_raw[];
    const uint32_t sbase = (smem_u32(smem_raw) + 1023u) & ~1023u;
    unsigned char* sptr = smem_raw + (sbase - smem_u32(smem_raw));

    const int warp = threadIdx.x >> 5, lane = threadIdx.x & 31;
    const uint32_t bar_full  = sbase + SM_BARS;
    const uint32_t bar_empty = bar_full + NSLOTS * 8;
    const uint32_t bar_jfull = bar_empty + NSLOTS * 8;
    const uint32_t bar_jfree = bar_jfull + JQ * 8;
    const uint32_t bar_epoch = bar_jfree + JQ * 8;
    volatile uint32_t* s_epoch = reinterpret_cast<volatile uint32_t*>(sptr + SM_EPOCH);
    volatile int4* meta = reinterpret_cast<volatile int4*>(sptr + SM_META);
    volatile int* jobq = reinterpret_cast<volatile int*>(sptr + SM_JOB);

    uint64_t pol = 0;
    if (threadIdx.x == NTHREADS - 32) {
        mbar_init(bar_full, 1);
        mbar_init(bar_full + 8, 1);
        asm volatile("fence.mbarrier_init.release.cluster;" ::: "memory");
        asm volatile("createpolicy.fractional.L2::evict_first.b64 %0, 1.0;" : "=l"(pol));
        int head, tile, cnt;
        decode_a((int)blockIdx.x, head, tile, cnt);
        const int row = head * SKV + tile * TILE_ROWS;
        meta[0].x = head; meta[0].y = tile; meta[0].w = (tile == NR) ? FLAG_EXTRA : 0;
        mbar_expect_tx(bar_full, TILE_BYTES + SQ * DH * 2);
        tma_load_2d(sbase + SM_TILES, &tmK, 0, row, bar_full, pol);
        tma_load_2d(sbase + SM_TILES + HALF_BYTES, &tmK, 64, row, bar_full, pol);
        mbar_expect_tx(bar_full + 8, TILE_BYTES);
        tma_load_2d(sbase + SM_TILES + TILE_BYTES, &tmV, 0, row, bar_full + 8, pol);
        tma_load_2d(sbase + SM_TILES + TILE_BYTES + HALF_BYTES, &tmV, 64, row, bar_full + 8, pol);
        bulk_load(sbase + SM_X, q + (size_t)head * SQ * DH, SQ * DH * 2, bar_full);
        for (int s = 2; s < NSLOTS; s++) mbar_init(bar_full + 8 * s, 1);
        for (int s = 0; s < NSLOTS; s++) mbar_init(bar_empty + 8 * s, NCW);
        for (int s = 0; s < JQ; s++) { mbar_init(bar_jfull + 8 * s, 1); mbar_init(bar_jfree + 8 * s, NEW); }
        mbar_init(bar_epoch, 1);
        asm volatile("fence.mbarrier_init.release.cluster;" ::: "memory");
    }
    __syncthreads();

    const float SC = 0.08838834764831845f * 1.4426950408889634f;

    if (warp == NCW + NEW) {
        if (lane == 0) {
            int nissued = 2;
            int job = 0;
            unsigned c = blockIdx.x + gridDim.x;
            while (c < (unsigned)NCHUNKS) {
                int head, tile, kind = 0;
                if (c < (unsigned)NA) {
                    int cnt;
                    decode_a((int)c, head, tile, cnt);
                    if (tile == NR) kind = FLAG_EXTRA;
                } else {
                    head = HD0 + ((int)c - NA); tile = NR; kind = FLAG_FINAL;
                }
#pragma unroll
                for (int z = 0; z < 2; z++) {
                    const int cc = (int)c - (z == 0 ? LAG : LAG_END);
                    if (cc >= 0 && cc < NA) {
                        int h2, t2, cnt2;
                        decode_a(cc, h2, t2, cnt2);
                        if (t2 == cnt2 - 1 && ((h2 >= NHEADS - HEADS_END) == (z == 1))) {
                            const int js = job % JQ;
                            mbar_wait(bar_jfree + 8 * js, ((job / JQ) & 1) ^ 1);
                            jobq[js] = h2;
                            mbar_arrive(bar_jfull + 8 * js);
                            job++;
                        }
                    }
                }
                const bool chk = (kind == 0) && head >= RING;
                const int row = head * SKV + tile * TILE_ROWS;
                unsigned long long tk = 0;
#pragma unroll
                for (int i = 0; i < 2; i++) {
                    const int slot = nissued % NSLOTS;
                    if (nissued > WIN) {
                        const int prev = nissued - WIN;
                        mbar_wait(bar_full + 8 * (prev % NSLOTS), (prev / NSLOTS) & 1);
                    }
                    mbar_wait(bar_empty + 8 * slot, ((nissued / NSLOTS) & 1) ^ 1);
                    const uint32_t fb = bar_full + 8 * slot, dst = sbase + SM_TILES + slot * TILE_BYTES;
                    if (i == 0) {
                        const uint32_t xb = sbase + SM_X + slot * XS_BYTES;
                        meta[slot].x = head; meta[slot].y = tile; meta[slot].w = kind;
                        mbar_expect_tx(fb, TILE_BYTES + SQ * DH * 2 + (kind == FLAG_FINAL ? REC_BYTES : 0) + (chk ? 16 : 0));
                        tma_load_2d(dst, &tmK, 0, row, fb, pol);
                        tma_load_2d(dst + HALF_BYTES, &tmK, 64, row, fb, pol);
                        bulk_load(xb, q + (size_t)head * SQ * DH, SQ * DH * 2, fb);
                        if (kind == FLAG_FINAL) bulk_load(xb + 1024, g_comb + (size_t)head * REC_FLOATS, REC_BYTES, fb);
                        if (chk) bulk_load(xb + 1024 + REC_BYTES, g_coll + COLL_STRIDE * (head - RING), 16, fb);
                        tk = global_ns();
                    } else {
                        while (global_ns() - tk < gap_ns) {}
                        mbar_expect_tx(fb, TILE_BYTES);
                        tma_load_2d(dst, &tmV, 0, row, fb, pol);
                        tma_load_2d(dst + HALF_BYTES, &tmV, 64, row, fb, pol);
                    }
                    nissued++;
                }
                c = atom_inc_relaxed(&g_work) + 2 * gridDim.x;
            }
            {
                const int js = job % JQ;
                mbar_wait(bar_jfree + 8 * js, ((job / JQ) & 1) ^ 1);
                jobq[js] = -1;
                mbar_arrive(bar_jfull + 8 * js);
            }
            {
                const int slot = nissued % NSLOTS;
                mbar_wait(bar_empty + 8 * slot, ((nissued / NSLOTS) & 1) ^ 1);
                meta[slot].w = FLAG_END;
                mbar_arrive(bar_full + 8 * slot);
            }
            mbar_wait(bar_epoch, 0);
            if (atom_inc_relaxed(&g_done) == gridDim.x - 1) { g_work = 0; g_done = 0; g_epoch = *s_epoch + 1u; }
        }
    } else if (warp < NCW) {
        const int g = lane >> 2, t = lane & 3, r8 = lane & 7;
        const uint32_t kOff = (uint32_t)((warp * 16 + r8 + ((lane >> 3) & 1) * 8) * 128 + (((lane >> 4) ^ r8) << 4));
        const uint32_t vOff = (uint32_t)((warp >> 2) * HALF_BYTES + (r8 + (lane >> 4) * 8) * 128 +
                                         (((((2 * warp) & 7) | ((lane >> 3) & 1)) ^ r8) << 4));
        float* wmax = reinterpret_cast<float*>(sptr + SM_WM);
        float* wsum = reinterpret_cast<float*>(sptr + SM_WS);
        uint2* pbuf = reinterpret_cast<uint2*>(sptr + SM_PB);
        const int tq = t & 1;
        const int dcol = warp * 16 + g;
        const int frag = (warp * 16 + g * 2 + tq) * 4;
        int slot = 0; uint32_t phase = 0;
        uint32_t epoch1 = 0u;
        while (true) {
            mbar_wait(bar_full + 8 * slot, phase);
            const int flags = meta[slot].w;
            if (flags & FLAG_END) break;
            const int head = meta[slot].x, tile = meta[slot].y;
            const uint32_t kb = sbase + SM_TILES + slot * TILE_BYTES;
            const unsigned char* xs = sptr + SM_X + slot * XS_BYTES;
            uint32_t kf[8][4];
#pragma unroll
            for (int j = 0; j < 8; j++)
                ldsm_x4(kf[j], kb + (j >> 2) * HALF_BYTES + (kOff ^ (uint32_t)(((2 * j) & 7) << 4)));
            uint32_t qf[8][2];
            {
                const uint32_t* qs = reinterpret_cast<const uint32_t*>(xs);
#pragma unroll
                for (int j = 0; j < 8; j++) {
                    qf[j][0] = (g < SQ) ? qs[g * 64 + j * 8 + t] : 0u;
                    qf[j][1] = (g < SQ) ? qs[g * 64 + j * 8 + 4 + t] : 0u;
                }
            }
            float4 cO = make_float4(0.f, 0.f, 0.f, 0.f), cML = make_float4(0.f, 0.f, 0.f, 0.f);
            if (flags & FLAG_FINAL) {
                const float* cs = reinterpret_cast<const float*>(xs + 1024);
                cO  = *reinterpret_cast<const float4*>(cs + frag);
                cML = *reinterpret_cast<const float4*>(cs + SQ * DH + tq * 4);
            }
            uint32_t freeflag = *reinterpret_cast<const uint32_t*>(xs + 1024 + REC_BYTES);
            __syncwarp();
            if (lane == 0) mbar_arrive(bar_empty + 8 * slot);
            if (++slot == NSLOTS) { slot = 0; phase ^= 1; }

            float sa[4] = {0.f, 0.f, 0.f, 0.f}, sb[4] = {0.f, 0.f, 0.f, 0.f};
#pragma unroll
            for (int j = 0; j < 8; j += 2) {
                mma_bf16(sa, kf[j], qf[j][0], qf[j][1]);
                mma_bf16(sb, kf[j + 1], qf[j + 1][0], qf[j + 1][1]);
            }
            const float s0 = sa[0] + sb[0], s1 = sa[1] + sb[1], s2 = sa[2] + sb[2], s3 = sa[3] + sb[3];
            float t0 = fmaxf(s0, s2), t1 = fmaxf(s1, s3);
#pragma unroll
            for (int x = 4; x <= 16; x <<= 1) {
                t0 = fmaxf(t0, __shfl_xor_sync(0xffffffffu, t0, x));
                t1 = fmaxf(t1, __shfl_xor_sync(0xffffffffu, t1, x));
            }
            if (lane < 2) *reinterpret_cast<float2*>(wmax + warp * 4 + lane * 2) = make_float2(t0, t1);
            named_bar_sync(2, NCW * 32);
            float m0 = -INFINITY, m1 = -INFINITY;
#pragma unroll
            for (int w = 0; w < NCW; w++) {
                const float2 x = *reinterpret_cast<const float2*>(wmax + w * 4 + tq * 2);
                m0 = fmaxf(m0, x.x); m1 = fmaxf(m1, x.y);
            }
            m0 = tagf(m0 * SC, 0u); m1 = tagf(m1 * SC, 0u);
            float p0 = ex2(fmaf(s0, SC, -m0)), p1 = ex2(fmaf(s1, SC, -m1));
            float p2 = ex2(fmaf(s2, SC, -m0)), p3 = ex2(fmaf(s3, SC, -m1));
            if (t >= 2) { p0 = p1 = p2 = p3 = 0.f; }
            {
                uint2 bb;
                bb.x = movmatrix_t(pack_bf16(p0, p1));
                bb.y = movmatrix_t(pack_bf16(p2, p3));
                pbuf[warp * 32 + lane] = bb;
                float r0 = p0 + p2, r1 = p1 + p3;
#pragma unroll
                for (int x = 4; x <= 16; x <<= 1) {
                    r0 += __shfl_xor_sync(0xffffffffu, r0, x);
                    r1 += __shfl_xor_sync(0xffffffffu, r1, x);
                }
                if (lane < 2) *reinterpret_cast<float2*>(wsum + warp * 4 + lane * 2) = make_float2(r0, r1);
            }
            named_bar_sync(2, NCW * 32);
            uint2 pf[8];
            float l0 = 0.f, l1 = 0.f;
#pragma unroll
            for (int w = 0; w < NCW; w++) {
                pf[w] = pbuf[w * 32 + lane];
                const float2 x = *reinterpret_cast<const float2*>(wsum + w * 4 + tq * 2);
                l0 += x.x; l1 += x.y;
            }
            if (epoch1 == 0u && (flags != 0 || head >= RING)) { mbar_wait(bar_epoch, 0); epoch1 = *s_epoch + 1u; }
            const uint32_t tag = (flags & (FLAG_EXTRA | FLAG_FINAL)) ? (epoch1 & 1u) : ring_tag(head);
            float fo0 = 1.f, fo1 = 1.f;
            float* rec = nullptr;
            if (flags & FLAG_FINAL) {
                const float* cg = g_comb + (size_t)head * REC_FLOATS;
                const long long tstart = clock64();
                while ((tag_bad(cO, tag) | tag_bad(cML, tag)) != 0u) {
                    cO  = ld_relaxed_v4(cg + frag);
                    cML = ld_relaxed_v4(cg + SQ * DH + tq * 4);
                    if (clock64() - tstart > SPIN_LIMIT) __trap();
                }
                cO = untag(cO); cML = untag(cML);
                const float M0 = fmaxf(m0, cML.x), M1 = fmaxf(m1, cML.z);
                const float a0 = ex2(m0 - M0), a1 = ex2(m1 - M1), c0 = ex2(cML.x - M0), c1 = ex2(cML.z - M1);
                const float i0 = 1.0f / fmaf(l0, a0, cML.y * c0), i1 = 1.0f / fmaf(l1, a1, cML.w * c1);
                fo0 = a0 * i0; fo1 = a1 * i1;
                cO.x *= c0 * i0; cO.y *= c1 * i1; cO.z *= c0 * i0; cO.w *= c1 * i1;
            } else if (flags & FLAG_EXTRA) {
                rec = g_comb + (size_t)head * REC_FLOATS;
            } else {
                rec = g_ring + ((size_t)(head % RING) * NR + tile) * REC_FLOATS;
                if (head >= RING) {
                    const long long tstart = clock64();
                    while (freeflag != epoch1) {
                        freeflag = ld_relaxed_u32(g_coll + COLL_STRIDE * (head - RING));
                        if (clock64() - tstart > SPIN_LIMIT) __trap();
                    }
                }
            }
            __syncwarp();

            mbar_wait(bar_full + 8 * slot, phase);
            const uint32_t vb = sbase + SM_TILES + slot * TILE_BYTES + vOff;
            uint32_t vf[8][4];
#pragma unroll
            for (int j = 0; j < 8; j++) ldsm_x4_t(vf[j], vb + j * 16 * 128);
            __syncwarp();
            if (lane == 0) mbar_arrive(bar_empty + 8 * slot);
            if (++slot == NSLOTS) { slot = 0; phase ^= 1; }
            float oa[4] = {0.f, 0.f, 0.f, 0.f}, ob[4] = {0.f, 0.f, 0.f, 0.f};
#pragma unroll
            for (int j = 0; j < 8; j += 2) {
                mma_bf16(oa, vf[j], pf[j].x, pf[j].y);
                mma_bf16(ob, vf[j + 1], pf[j + 1].x, pf[j + 1].y);
            }
            if (t < 2) {
                if (flags & FLAG_FINAL) {
                    __nv_bfloat16* op = out + ((size_t)head * SQ + 2 * t) * DH + dcol;
                    op[0]      = __float2bfloat16(fmaf(oa[0] + ob[0], fo0, cO.x));
                    op[DH]     = __float2bfloat16(fmaf(oa[1] + ob[1], fo1, cO.y));
                    op[8]      = __float2bfloat16(fmaf(oa[2] + ob[2], fo0, cO.z));
                    op[DH + 8] = __float2bfloat16(fmaf(oa[3] + ob[3], fo1, cO.w));
                } else {
                    st_relaxed_v4(rec + frag, tagf(oa[0] + ob[0], tag), tagf(oa[1] + ob[1], tag),
                                  tagf(oa[2] + ob[2], tag), tagf(oa[3] + ob[3], tag));
                    if (threadIdx.x < 2) st_relaxed_v4(rec + SQ * DH + t * 4, tagf(m0, tag), tagf(l0, tag), tagf(m1, tag), tagf(l1, tag));
                }
            }
        }
    } else {
        const int e = threadIdx.x - NCW * 32;
        const int half = e >> 7;
        const int f = e & 127;
        const int tq = lane & 1;
        float* cx = reinterpret_cast<float*>(sptr + SM_CX);
        if (e == 0) {
            *s_epoch = ld_relaxed_u32(&g_epoch);
            mbar_arrive(bar_epoch);
        }
        mbar_wait(bar_epoch, 0);
        const uint32_t epoch1 = *s_epoch + 1u;
        const uint32_t etag = epoch1 & 1u;
        for (int k = 0;; k++) {
            const int js = k % JQ; const uint32_t jph = (k / JQ) & 1;
            mbar_wait(bar_jfull + 8 * js, jph);
            const int head = jobq[js];
            __syncwarp();
            if (lane == 0) mbar_arrive(bar_jfree + 8 * js);
            if (head < 0) break;
            const bool deferred = is_deferred(head);
            const uint32_t rtag = ring_tag(head);
            const int nrec_all = deferred ? NR : NR + 1;
            const int r0 = half * HREC;
            const int nrec = (nrec_all - r0 < HREC) ? (nrec_all - r0) : HREC;
            const float* ring = g_ring + ((size_t)(head % RING) * NR + r0) * REC_FLOATS;
            float* comb = g_comb + (size_t)head * REC_FLOATS;
            const int ml_u = lane & 15;
            const bool ml_extra = (r0 + ml_u == NR);
            const float* pml = (ml_extra ? comb : ring + (size_t)ml_u * REC_FLOATS) + SQ * DH + (lane >> 4) * 4;
            const uint32_t mltag = ml_extra ? etag : rtag;
            float4 v[HREC];
#pragma unroll
            for (int u = 0; u < HREC; u++) v[u] = make_float4(0.f, 0.f, 0.f, 0.f);
            float4 pm = make_float4(-INFINITY, 0.f, -INFINITY, 0.f);
            uint32_t pending = (1u << nrec) - 1u;
            const long long tstart = clock64();
            while (true) {
                if ((pending >> ml_u) & 1u) pm = ld_relaxed_v4(pml);
#pragma unroll
                for (int u = 0; u < HREC; u++)
                    if ((pending >> u) & 1u)
                        v[u] = ld_relaxed_v4(((r0 + u == NR) ? comb : ring + (size_t)u * REC_FLOATS) + f * 4);
                uint32_t bad = tag_bad(pm, mltag) << ml_u;
#pragma unroll
                for (int u = 0; u < HREC; u++) bad |= tag_bad(v[u], (r0 + u == NR) ? etag : rtag) << u;
                pending &= __reduce_or_sync(0xffffffffu, bad);
                if (pending == 0u) break;
                if (clock64() - tstart > SPIN_LIMIT) __trap();
                __nanosleep(500);
            }
            pm = untag(pm);
            const bool mlv = ml_u < nrec;
            float Ma = mlv ? pm.x : -INFINITY, Mb = mlv ? pm.z : -INFINITY;
#pragma unroll
            for (int x = 1; x < 16; x <<= 1) {
                Ma = fmaxf(Ma, __shfl_xor_sync(0xffffffffu, Ma, x));
                Mb = fmaxf(Mb, __shfl_xor_sync(0xffffffffu, Mb, x));
            }
            const float sca = mlv ? ex2(pm.x - Ma) : 0.f, scb = mlv ? ex2(pm.z - Mb) : 0.f;
            float La = mlv ? pm.y * sca : 0.f, Lb = mlv ? pm.w * scb : 0.f;
#pragma unroll
            for (int x = 1; x < 16; x <<= 1) {
                La += __shfl_xor_sync(0xffffffffu, La, x);
                Lb += __shfl_xor_sync(0xffffffffu, Lb, x);
            }
            float4 acc = make_float4(0.f, 0.f, 0.f, 0.f);
#pragma unroll
            for (int u = 0; u < HREC; u++) {
                const float sa = __shfl_sync(0xffffffffu, sca, u + 16 * tq), sb = __shfl_sync(0xffffffffu, scb, u + 16 * tq);
                const float4 x = untag(v[u]);
                acc.x = fmaf(x.x, sa, acc.x); acc.y = fmaf(x.y, sb, acc.y);
                acc.z = fmaf(x.z, sa, acc.z); acc.w = fmaf(x.w, sb, acc.w);
            }
            Ma = __shfl_sync(0xffffffffu, Ma, 16 * tq); La = __shfl_sync(0xffffffffu, La, 16 * tq);
            Mb = __shfl_sync(0xffffffffu, Mb, 16 * tq); Lb = __shfl_sync(0xffffffffu, Lb, 16 * tq);
            if (half == 1) {
                *reinterpret_cast<float4*>(cx + f * 4) = acc;
                if (f < 2) *reinterpret_cast<float4*>(cx + SQ * DH + tq * 4) = make_float4(Ma, La, Mb, Lb);
            }
            named_bar_sync(1, NEW * 32);
            if (e == NEW * 32 - 1) st_relaxed_u32(g_coll + COLL_STRIDE * head, epoch1);
            if (half == 0) {
                const float4 ov = *reinterpret_cast<const float4*>(cx + f * 4);
                const float4 oml = *reinterpret_cast<const float4*>(cx + SQ * DH + tq * 4);
                const float M0 = fmaxf(Ma, oml.x), M1 = fmaxf(Mb, oml.z);
                const float fa0 = ex2(Ma - M0), fb0 = ex2(oml.x - M0), fa1 = ex2(Mb - M1), fb1 = ex2(oml.z - M1);
                const float L0 = fmaf(La, fa0, oml.y * fb0), L1 = fmaf(Lb, fa1, oml.w * fb1);
                const float r0x = fmaf(acc.x, fa0, ov.x * fb0), r1x = fmaf(acc.y, fa1, ov.y * fb1);
                const float r0y = fmaf(acc.z, fa0, ov.z * fb0), r1y = fmaf(acc.w, fa1, ov.w * fb1);
                if (deferred) {
                    st_relaxed_v4(comb + f * 4, tagf(r0x, etag), tagf(r1x, etag), tagf(r0y, etag), tagf(r1y, etag));
                    if (f < 2) st_relaxed_v4(comb + SQ * DH + tq * 4, tagf(M0, etag), tagf(L0, etag), tagf(M1, etag), tagf(L1, etag));
                } else {
                    const float i0 = 1.0f / L0, i1 = 1.0f / L1;
                    __nv_bfloat16* op = out + ((size_t)head * SQ + 2 * tq) * DH + (f >> 4) * 16 + ((f >> 1) & 7);
                    op[0]      = __float2bfloat16(r0x * i0);
                    op[DH]     = __float2bfloat16(r1x * i1);
                    op[8]      = __float2bfloat16(r0y * i0);
                    op[DH + 8] = __float2bfloat16(r1y * i1);
                }
            }
            named_bar_sync(1, NEW * 32);
        }
    }
}

typedef CUresult (*EncodeTiledFn)(CUtensorMap*, CUtensorMapDataType, cuuint32_t, void*, const cuuint64_t*,
                                  const cuuint64_t*, const cuuint32_t*, const cuuint32_t*, CUtensorMapInterleave,
                                  CUtensorMapSwizzle, CUtensorMapL2promotion, CUtensorMapFloatOOBfill);

void make_map(EncodeTiledFn enc, CUtensorMap* m, void* p) {
    cuuint64_t dims[2]    = {(cuuint64_t)DH, (cuuint64_t)NHEADS * SKV};
    cuuint64_t strides[1] = {(cuuint64_t)DH * 2};
    cuuint32_t box[2]     = {64, (cuuint32_t)TILE_ROWS};
    cuuint32_t es[2]      = {1, 1};
    enc(m, CU_TENSOR_MAP_DATA_TYPE_BFLOAT16, 2, p, dims, strides, box, es, CU_TENSOR_MAP_INTERLEAVE_NONE,
        CU_TENSOR_MAP_SWIZZLE_128B, CU_TENSOR_MAP_L2_PROMOTION_L2_256B, CU_TENSOR_MAP_FLOAT_OOB_FILL_NONE);
}

}

extern "C" void kernel_launch(void* const* d_in, const int* in_sizes, int n_in, void* d_out, int out_size) {
    (void)in_sizes; (void)n_in; (void)out_size;
    static EncodeTiledFn enc = nullptr;
    static int nsm = 0;
    static unsigned gap_ns = 0;
    if (!enc) {
        cudaDriverEntryPointQueryResult qr;
        void* fn = nullptr;
        cudaGetDriverEntryPoint("cuTensorMapEncodeTiled", &fn, cudaEnableDefault, &qr);
        enc = (EncodeTiledFn)fn;
        cudaFuncSetAttribute(attn_decode_kernel, cudaFuncAttributeMaxDynamicSharedMemorySize, SMEM_BYTES);
        int dev = 0;
        cudaGetDevice(&dev);
        cudaDeviceGetAttribute(&nsm, cudaDevAttrMultiProcessorCount, dev);
        int mem_khz = 0, bus_bits = 0;
        cudaDeviceGetAttribute(&mem_khz, cudaDevAttrMemoryClockRate, dev);
        cudaDeviceGetAttribute(&bus_bits, cudaDevAttrGlobalMemoryBusWidth, dev);
        const double bw = 2.0 * mem_khz * 1e3 * bus_bits / 8.0 * 0.96;
        const int g = nsm < MAX_CTA ? nsm : MAX_CTA;
        double gap = bw > 0.0 ? (double)g * 2.0 * TILE_BYTES / bw * 1e9 - GAP_FIXED_NS : 0.0;
        gap_ns = gap < 0.0 ? 0u : gap > 1200.0 ? 1200u : (unsigned)gap;
    }
    CUtensorMap tmK, tmV;
    make_map(enc, &tmK, d_in[1]);
    make_map(enc, &tmV, d_in[2]);
    const int grid = nsm < MAX_CTA ? nsm : MAX_CTA;
    attn_decode_kernel<<<grid, NTHREADS, SMEM_BYTES>>>(tmK, tmV, (const __nv_bfloat16*)d_in[0], (__nv_bfloat16*)d_out, gap_ns);
}
```

```cpp
#include <cuda_runtime.h>
#include <cuda_bf16.h>
#include <cuda.h>
#include <stdint.h>

namespace {

constexpr int NHEADS = 512;
constexpr int SQ     = 4;
constexpr int SKV    = 4096;
constexpr int DH     = 128;

constexpr int TILE_ROWS  = 128;
constexpr int TILE_BYTES = TILE_ROWS * DH * 2;
constexpr int HALF_BYTES = TILE_BYTES / 2;
constexpr int TPH    = SKV / TILE_ROWS;
constexpr int NSLOTS = 4;
constexpr int WIN    = 2;
constexpr int NCW = 8;
constexpr int NEW = 8;
constexpr int NTHREADS = 32 * (NCW + NEW + 1);
constexpr int MAX_CTA = 132;
constexpr double GAP_FIXED_NS = 1600.0;

constexpr int NR   = TPH - 1;
constexpr int TH   = 500;
constexpr int GAP  = 12;
constexpr int HD0  = NHEADS - GAP - TH;
constexpr int NA1  = HD0 * (NR + 1);
constexpr int NA2  = NA1 + TH * NR;
constexpr int NA   = NA2 + GAP * (NR + 1);
constexpr int NCHUNKS = NA + TH;
constexpr int LAG  = 480;
constexpr int LAG_END = 420, HEADS_END = 20;
constexpr int RING = 32;
constexpr int HREC = (NR + 2) / 2;
static_assert(HD0 >= 0 && LAG_END <= TH && LAG <= TH + HEADS_END * NR && LAG < RING * NR && LAG_END < RING * NR &&
              NHEADS % (2 * RING) == 0 && HREC <= 16 && 2 * MAX_CTA <= LAG_END && 2 * MAX_CTA <= RING * NR &&
              WIN + 1 <= NSLOTS, "bad schedule");

constexpr int JQ = 4;
constexpr int REC_BYTES  = SQ * DH * 4 + SQ * 8;
constexpr int REC_FLOATS = 544;

constexpr int SM_TILES = 0;
constexpr int SM_Q     = SM_TILES + NSLOTS * TILE_BYTES;
constexpr int SM_X     = SM_Q + NSLOTS * 1024 - 1024;
constexpr int XS_BYTES = REC_BYTES + 16 + 16;
constexpr int SM_PB    = SM_X + 1024 + NSLOTS * XS_BYTES;
constexpr int SM_WM    = SM_PB + NCW * 32 * 8;
constexpr int SM_WS    = SM_WM + NCW * SQ * 4;
constexpr int SM_CX    = SM_WS + NCW * SQ * 4;
constexpr int SM_META  = SM_CX + REC_BYTES;
constexpr int SM_JOB   = SM_META + NSLOTS * 16;
constexpr int SM_EPOCH = SM_JOB + JQ * 4;
constexpr int SM_BARS  = SM_EPOCH + 16;
constexpr int SM_TOTAL = SM_BARS + (2 * NSLOTS + 2 * JQ + 1) * 8;
constexpr int SMEM_BYTES = SM_TOTAL + 1024;
static_assert(REC_BYTES % 16 == 0 && XS_BYTES % 16 == 0 && SM_BARS % 8 == 0, "align");

constexpr int FLAG_END = 4, FLAG_EXTRA = 8, FLAG_FINAL = 16;

constexpr int COLL_STRIDE = 4;
struct Scratch {
    float ring[(size_t)RING * NR * REC_FLOATS];
    float comb[(size_t)NHEADS * REC_FLOATS];
    unsigned int coll[NHEADS * COLL_STRIDE];
    unsigned int pad0[64];
    unsigned int work;
    unsigned int pad1[63];
    unsigned int done;
    unsigned int pad2[63];
    unsigned int epoch;
};
union ScratchBlob { Scratch s; unsigned char bytes[4 << 20]; };
static_assert(sizeof(Scratch) <= sizeof(ScratchBlob), "scratch");
__device__ __align__(256) ScratchBlob g_scratch;
#define g_ring  (g_scratch.s.ring)
#define g_comb  (g_scratch.s.comb)
#define g_coll  (g_scratch.s.coll)
#define g_work  (g_scratch.s.work)
#define g_done  (g_scratch.s.done)
#define g_epoch (g_scratch.s.epoch)

__device__ __forceinline__ uint32_t smem_u32(const void* p) { return (uint32_t)__cvta_generic_to_shared(p); }
__device__ __forceinline__ void mbar_init(uint32_t bar, uint32_t cnt) {
    asm volatile("mbarrier.init.shared::cta.b64 [%0], %1;" :: "r"(bar), "r"(cnt) : "memory");
}
__device__ __forceinline__ void mbar_expect_tx(uint32_t bar, uint32_t bytes) {
    asm volatile("mbarrier.arrive.expect_tx.shared::cta.b64 _, [%0], %1;" :: "r"(bar), "r"(bytes) : "memory");
}
__device__ __forceinline__ void mbar_arrive(uint32_t bar) {
    asm volatile("mbarrier.arrive.shared::cta.b64 _, [%0];" :: "r"(bar) : "memory");
}
__device__ __forceinline__ bool mbar_try_wait(uint32_t bar, uint32_t parity) {
    uint32_t ok;
    asm volatile("{\n.reg .pred p;\nmbarrier.try_wait.parity.shared::cta.b64 p, [%1], %2;\nselp.u32 %0, 1, 0, p;\n}"
                 : "=r"(ok) : "r"(bar), "r"(parity) : "memory");
    return ok != 0;
}
constexpr long long SPIN_LIMIT = 4000000000LL;
__device__ __forceinline__ void mbar_wait(uint32_t bar, uint32_t parity) {
    if (mbar_try_wait(bar, parity)) return;
    const long long t0 = clock64();
    while (!mbar_try_wait(bar, parity)) {
        if (clock64() - t0 > SPIN_LIMIT) __trap();
    }
}
__device__ __forceinline__ void tma_load_2d(uint32_t dst, const CUtensorMap* tm, int c0, int c1, uint32_t bar, uint64_t pol) {
    asm volatile("cp.async.bulk.tensor.2d.shared::cluster.global.mbarrier::complete_tx::bytes.L2::cache_hint [%0], [%1, {%3, %4}], [%2], %5;"
                 :: "r"(dst), "l"(tm), "r"(bar), "r"(c0), "r"(c1), "l"(pol) : "memory");
}
__device__ __forceinline__ void tma_load_2d_nh(uint32_t dst, const CUtensorMap* tm, int c0, int c1, uint32_t bar) {
    asm volatile("cp.async.bulk.tensor.2d.shared::cluster.global.mbarrier::complete_tx::bytes [%0], [%1, {%3, %4}], [%2];"
                 :: "r"(dst), "l"(tm), "r"(bar), "r"(c0), "r"(c1) : "memory");
}
__device__ __forceinline__ void bulk_load(uint32_t dst, const void* src, uint32_t bytes, uint32_t bar) {
    asm volatile("cp.async.bulk.shared::cluster.global.mbarrier::complete_tx::bytes [%0], [%1], %2, [%3];"
                 :: "r"(dst), "l"(src), "r"(bytes), "r"(bar) : "memory");
}
__device__ __forceinline__ void ldsm_x4(uint32_t (&r)[4], uint32_t addr) {
    asm volatile("ldmatrix.sync.aligned.m8n8.x4.shared.b16 {%0,%1,%2,%3}, [%4];"
                 : "=r"(r[0]), "=r"(r[1]), "=r"(r[2]), "=r"(r[3]) : "r"(addr) : "memory");
}
__device__ __forceinline__ void ldsm_x4_t(uint32_t (&r)[4], uint32_t addr) {
    asm volatile("ldmatrix.sync.aligned.m8n8.x4.trans.shared.b16 {%0,%1,%2,%3}, [%4];"
                 : "=r"(r[0]), "=r"(r[1]), "=r"(r[2]), "=r"(r[3]) : "r"(addr) : "memory");
}
__device__ __forceinline__ void mma_bf16(float (&d)[4], const uint32_t (&a)[4], uint32_t b0, uint32_t b1) {
    asm volatile("mma.sync.aligned.m16n8k16.row.col.f32.bf16.bf16.f32 {%0,%1,%2,%3}, {%4,%5,%6,%7}, {%8,%9}, {%0,%1,%2,%3};"
                 : "+f"(d[0]), "+f"(d[1]), "+f"(d[2]), "+f"(d[3])
                 : "r"(a[0]), "r"(a[1]), "r"(a[2]), "r"(a[3]), "r"(b0), "r"(b1));
}
__device__ __forceinline__ uint32_t movmatrix_t(uint32_t a) {
    uint32_t d;
    asm volatile("movmatrix.sync.aligned.m8n8.trans.b16 %0, %1;" : "=r"(d) : "r"(a));
    return d;
}
__device__ __forceinline__ uint32_t pack_bf16(float lo, float hi) {
    uint32_t d;
    asm("cvt.rn.bf16x2.f32 %0, %1, %2;" : "=r"(d) : "f"(hi), "f"(lo));
    return d;
}
__device__ __forceinline__ float ex2(float x) {
    float y;
    asm("ex2.approx.ftz.f32 %0, %1;" : "=f"(y) : "f"(x));
    return y;
}
__device__ __forceinline__ void named_bar_sync(int id, int nthreads) {
    asm volatile("bar.sync %0, %1;" :: "r"(id), "r"(nthreads) : "memory");
}
__device__ __forceinline__ unsigned atom_inc_relaxed(unsigned int* p) {
    unsigned o;
    asm volatile("atom.relaxed.gpu.global.add.u32 %0, [%1], 1;" : "=r"(o) : "l"(p) : "memory");
    return o;
}
__device__ __forceinline__ unsigned long long global_ns() {
    unsigned long long t;
    asm volatile("mov.u64 %0, %globaltimer;" : "=l"(t));
    return t;
}
__device__ __forceinline__ uint32_t fbits(float x) { return __float_as_uint(x); }
__device__ __forceinline__ float tagf(float x, uint32_t tag) { return __uint_as_float((fbits(x) & ~1u) | tag); }
__device__ __forceinline__ float4 untag(const float4& v) {
    return make_float4(tagf(v.x, 0u), tagf(v.y, 0u), tagf(v.z, 0u), tagf(v.w, 0u));
}
__device__ __forceinline__ uint32_t tag_bad(const float4& v, uint32_t tag) {
    return ((fbits(v.x) ^ tag) | (fbits(v.y) ^ tag) | (fbits(v.z) ^ tag) | (fbits(v.w) ^ tag)) & 1u;
}
__device__ __forceinline__ void st_relaxed_u32(unsigned int* p, uint32_t x) {
    asm volatile("st.relaxed.gpu.global.u32 [%0], %1;" :: "l"(p), "r"(x) : "memory");
}
__device__ __forceinline__ void st_relaxed_v4(float* p, float x, float y, float z, float w) {
    asm volatile("st.relaxed.gpu.global.v4.f32 [%0], {%1, %2, %3, %4};" :: "l"(p), "f"(x), "f"(y), "f"(z), "f"(w) : "memory");
}
__device__ __forceinline__ uint32_t ld_relaxed_u32(const unsigned int* p) {
    uint32_t v;
    asm volatile("ld.relaxed.gpu.global.u32 %0, [%1];" : "=r"(v) : "l"(p) : "memory");
    return v;
}
__device__ __forceinline__ float4 ld_relaxed_v4(const float* p) {
    float4 v;
    asm volatile("ld.relaxed.gpu.global.v4.f32 {%0,%1,%2,%3}, [%4];" : "=f"(v.x), "=f"(v.y), "=f"(v.z), "=f"(v.w) : "l"(p) : "memory");
    return v;
}

__device__ __forceinline__ void decode_a(int c, int& head, int& tile, int& cnt) {
    if (c < NA1)      { cnt = NR + 1; head = c / (NR + 1); tile = c % (NR + 1); }
    else if (c < NA2) { cnt = NR;     head = HD0 + (c - NA1) / NR; tile = (c - NA1) % NR; }
    else              { cnt = NR + 1; head = HD0 + TH + (c - NA2) / (NR + 1); tile = (c - NA2) % (NR + 1); }
}
__device__ __forceinline__ bool is_deferred(int head) { return head >= HD0 && head < HD0 + TH; }
__device__ __forceinline__ uint32_t ring_tag(int head) { return (uint32_t)(head / RING + 1) & 1u; }

__global__ void __launch_bounds__(NTHREADS, 1)
attn_decode_kernel(const __grid_constant__ CUtensorMap tmK, const __grid_constant__ CUtensorMap tmV,
                   const __grid_constant__ CUtensorMap tmQ, __nv_bfloat16* __restrict__ out, const unsigned gap_ns)
{
    extern __shared__ unsigned char smem_raw[];
    const uint32_t sbase = (smem_u32(smem_raw) + 1023u) & ~1023u;
    unsigned char* sptr = smem_raw + (sbase - smem_u32(smem_raw));

    const int warp = threadIdx.x >> 5, lane = threadIdx.x & 31;
    const uint32_t bar_full  = sbase + SM_BARS;
    const uint32_t bar_empty = bar_full + NSLOTS * 8;
    const uint32_t bar_jfull = bar_empty + NSLOTS * 8;
    const uint32_t bar_jfree = bar_jfull + JQ * 8;
    const uint32_t bar_epoch = bar_jfree + JQ * 8;
    volatile uint32_t* s_epoch = reinterpret_cast<volatile uint32_t*>(sptr + SM_EPOCH);
    volatile int4* meta = reinterpret_cast<volatile int4*>(sptr + SM_META);
    volatile int* jobq = reinterpret_cast<volatile int*>(sptr + SM_JOB);

    uint64_t pol = 0;
    if (threadIdx.x == NTHREADS - 32) {
        mbar_init(bar_full, 1);
        mbar_init(bar_full + 8, 1);
        asm volatile("fence.mbarrier_init.release.cluster;" ::: "memory");
        asm volatile("createpolicy.fractional.L2::evict_first.b64 %0, 1.0;" : "=l"(pol));
        int head, tile, cnt;
        decode_a((int)blockIdx.x, head, tile, cnt);
        const int row = head * SKV + tile * TILE_ROWS;
        meta[0].x = head; meta[0].y = tile; meta[0].w = (tile == NR) ? FLAG_EXTRA : 0;
        mbar_expect_tx(bar_full, TILE_BYTES + SQ * DH * 2);
        tma_load_2d(sbase + SM_TILES, &tmK, 0, row, bar_full, pol);
        tma_load_2d(sbase + SM_TILES + HALF_BYTES, &tmK, 64, row, bar_full, pol);
        mbar_expect_tx(bar_full + 8, TILE_BYTES);
        tma_load_2d(sbase + SM_TILES + TILE_BYTES, &tmV, 0, row, bar_full + 8, pol);
        tma_load_2d(sbase + SM_TILES + TILE_BYTES + HALF_BYTES, &tmV, 64, row, bar_full + 8, pol);
        tma_load_2d_nh(sbase + SM_Q, &tmQ, 0, head * 8, bar_full);
        for (int s = 2; s < NSLOTS; s++) mbar_init(bar_full + 8 * s, 1);
        for (int s = 0; s < NSLOTS; s++) mbar_init(bar_empty + 8 * s, NCW);
        for (int s = 0; s < JQ; s++) { mbar_init(bar_jfull + 8 * s, 1); mbar_init(bar_jfree + 8 * s, NEW); }
        mbar_init(bar_epoch, 1);
        asm volatile("fence.mbarrier_init.release.cluster;" ::: "memory");
    }
    __syncthreads();

    const float SC = 0.08838834764831845f * 1.4426950408889634f;

    if (warp == NCW + NEW) {
        if (lane == 0) {
            int nissued = 2;
            int job = 0;
            unsigned c = blockIdx.x + gridDim.x;
            while (c < (unsigned)NCHUNKS) {
                int head, tile, kind = 0;
                if (c < (unsigned)NA) {
                    int cnt;
                    decode_a((int)c, head, tile, cnt);
                    if (tile == NR) kind = FLAG_EXTRA;
                } else {
                    head = HD0 + ((int)c - NA); tile = NR; kind = FLAG_FINAL;
                }
#pragma unroll
                for (int z = 0; z < 2; z++) {
                    const int cc = (int)c - (z == 0 ? LAG : LAG_END);
                    if (cc >= 0 && cc < NA) {
                        int h2, t2, cnt2;
                        decode_a(cc, h2, t2, cnt2);
                        if (t2 == cnt2 - 1 && ((h2 >= NHEADS - HEADS_END) == (z == 1))) {
                            const int js = job % JQ;
                            mbar_wait(bar_jfree + 8 * js, ((job / JQ) & 1) ^ 1);
                            jobq[js] = h2;
                            mbar_arrive(bar_jfull + 8 * js);
                            job++;
                        }
                    }
                }
                const bool chk = (kind == 0) && head >= RING;
                const int row = head * SKV + tile * TILE_ROWS;
                unsigned long long tk = 0;
#pragma unroll
                for (int i = 0; i < 2; i++) {
                    const int slot = nissued % NSLOTS;
                    if (nissued > WIN) {
                        const int prev = nissued - WIN;
                        mbar_wait(bar_full + 8 * (prev % NSLOTS), (prev / NSLOTS) & 1);
                    }
                    mbar_wait(bar_empty + 8 * slot, ((nissued / NSLOTS) & 1) ^ 1);
                    const uint32_t fb = bar_full + 8 * slot, dst = sbase + SM_TILES + slot * TILE_BYTES;
                    if (i == 0) {
                        const uint32_t xb = sbase + SM_X + slot * XS_BYTES;
                        meta[slot].x = head; meta[slot].y = tile; meta[slot].w = kind;
                        mbar_expect_tx(fb, TILE_BYTES + SQ * DH * 2 + (kind == FLAG_FINAL ? REC_BYTES : 0) + (chk ? 16 : 0));
                        tma_load_2d(dst, &tmK, 0, row, fb, pol);
                        tma_load_2d(dst + HALF_BYTES, &tmK, 64, row, fb, pol);
                        tma_load_2d_nh(sbase + SM_Q + slot * 1024, &tmQ, 0, head * 8, fb);
                        if (kind == FLAG_FINAL) bulk_load(xb + 1024, g_comb + (size_t)head * REC_FLOATS, REC_BYTES, fb);
                        if (chk) bulk_load(xb + 1024 + REC_BYTES, g_coll + COLL_STRIDE * (head - RING), 16, fb);
                        tk = global_ns();
                    } else {
                        while (global_ns() - tk < gap_ns) {}
                        mbar_expect_tx(fb, TILE_BYTES);
                        tma_load_2d(dst, &tmV, 0, row, fb, pol);
                        tma_load_2d(dst + HALF_BYTES, &tmV, 64, row, fb, pol);
                    }
                    nissued++;
                }
                c = atom_inc_relaxed(&g_work) + 2 * gridDim.x;
            }
            {
                const int js = job % JQ;
                mbar_wait(bar_jfree + 8 * js, ((job / JQ) & 1) ^ 1);
                jobq[js] = -1;
                mbar_arrive(bar_jfull + 8 * js);
            }
            {
                const int slot = nissued % NSLOTS;
                mbar_wait(bar_empty + 8 * slot, ((nissued / NSLOTS) & 1) ^ 1);
                meta[slot].w = FLAG_END;
                mbar_arrive(bar_full + 8 * slot);
            }
            mbar_wait(bar_epoch, 0);
            if (atom_inc_relaxed(&g_done) == gridDim.x - 1) { g_work = 0; g_done = 0; g_epoch = *s_epoch + 1u; }
        }
    } else if (warp < NCW) {
        const int g = lane >> 2, t = lane & 3, r8 = lane & 7;
        const uint32_t kOff = (uint32_t)((warp * 16 + r8 + ((lane >> 3) & 1) * 8) * 128 + (((lane >> 4) ^ r8) << 4));
        const uint32_t vOff = (uint32_t)((warp >> 2) * HALF_BYTES + (r8 + (lane >> 4) * 8) * 128 +
                                         (((((2 * warp) & 7) | ((lane >> 3) & 1)) ^ r8) << 4));
        float* wmax = reinterpret_cast<float*>(sptr + SM_WM);
        float* wsum = reinterpret_cast<float*>(sptr + SM_WS);
        uint2* pbuf = reinterpret_cast<uint2*>(sptr + SM_PB);
        const int tq = t & 1;
        const int dcol = warp * 16 + g;
        const int frag = (warp * 16 + g * 2 + tq) * 4;
        int slot = 0; uint32_t phase = 0;
        uint32_t epoch1 = 0u;
        while (true) {
            mbar_wait(bar_full + 8 * slot, phase);
            const int flags = meta[slot].w;
            if (flags & FLAG_END) break;
            const int head = meta[slot].x, tile = meta[slot].y;
            const uint32_t kb = sbase + SM_TILES + slot * TILE_BYTES;
            const unsigned char* xs = sptr + SM_X + slot * XS_BYTES;
            uint32_t kf[8][4];
#pragma unroll
            for (int j = 0; j < 8; j++)
                ldsm_x4(kf[j], kb + (j >> 2) * HALF_BYTES + (kOff ^ (uint32_t)(((2 * j) & 7) << 4)));
            uint32_t qf[4][4];
#pragma unroll
            for (int i = 0; i < 4; i++) {
                const int hr = 2 * (lane & 3) + (i >> 1);
                const int cc = ((i & 1) * 4 + (lane >> 3));
                ldsm_x4(qf[i], sbase + SM_Q + slot * 1024 + hr * 128 + ((cc ^ hr) << 4));
            }
            float4 cO = make_float4(0.f, 0.f, 0.f, 0.f), cML = make_float4(0.f, 0.f, 0.f, 0.f);
            if (flags & FLAG_FINAL) {
                const float* cs = reinterpret_cast<const float*>(xs + 1024);
                cO  = *reinterpret_cast<const float4*>(cs + frag);
                cML = *reinterpret_cast<const float4*>(cs + SQ * DH + tq * 4);
            }
            uint32_t freeflag = *reinterpret_cast<const uint32_t*>(xs + 1024 + REC_BYTES);
            __syncwarp();
            if (lane == 0) mbar_arrive(bar_empty + 8 * slot);
            if (++slot == NSLOTS) { slot = 0; phase ^= 1; }

            float sa[4] = {0.f, 0.f, 0.f, 0.f}, sb[4] = {0.f, 0.f, 0.f, 0.f};
#pragma unroll
            for (int j = 0; j < 8; j += 2) {
                mma_bf16(sa, kf[j], qf[j >> 1][0], qf[j >> 1][1]);
                mma_bf16(sb, kf[j + 1], qf[j >> 1][2], qf[j >> 1][3]);
            }
            const float s0 = sa[0] + sb[0], s1 = sa[1] + sb[1], s2 = sa[2] + sb[2], s3 = sa[3] + sb[3];
            float t0 = fmaxf(s0, s2), t1 = fmaxf(s1, s3);
#pragma unroll
            for (int x = 4; x <= 16; x <<= 1) {
                t0 = fmaxf(t0, __shfl_xor_sync(0xffffffffu, t0, x));
                t1 = fmaxf(t1, __shfl_xor_sync(0xffffffffu, t1, x));
            }
            if (lane < 2) *reinterpret_cast<float2*>(wmax + warp * 4 + lane * 2) = make_float2(t0, t1);
            named_bar_sync(2, NCW * 32);
            float m0 = -INFINITY, m1 = -INFINITY;
#pragma unroll
            for (int w = 0; w < NCW; w++) {
                const float2 x = *reinterpret_cast<const float2*>(wmax + w * 4 + tq * 2);
                m0 = fmaxf(m0, x.x); m1 = fmaxf(m1, x.y);
            }
            m0 = tagf(m0 * SC, 0u); m1 = tagf(m1 * SC, 0u);
            float p0 = ex2(fmaf(s0, SC, -m0)), p1 = ex2(fmaf(s1, SC, -m1));
            float p2 = ex2(fmaf(s2, SC, -m0)), p3 = ex2(fmaf(s3, SC, -m1));
            if (t >= 2) { p0 = p1 = p2 = p3 = 0.f; }
            {
                uint2 bb;
                bb.x = movmatrix_t(pack_bf16(p0, p1));
                bb.y = movmatrix_t(pack_bf16(p2, p3));
                pbuf[warp * 32 + lane] = bb;
                float r0 = p0 + p2, r1 = p1 + p3;
#pragma unroll
                for (int x = 4; x <= 16; x <<= 1) {
                    r0 += __shfl_xor_sync(0xffffffffu, r0, x);
                    r1 += __shfl_xor_sync(0xffffffffu, r1, x);
                }
                if (lane < 2) *reinterpret_cast<float2*>(wsum + warp * 4 + lane * 2) = make_float2(r0, r1);
            }
            named_bar_sync(2, NCW * 32);
            uint2 pf[8];
            float l0 = 0.f, l1 = 0.f;
#pragma unroll
            for (int w = 0; w < NCW; w++) {
                pf[w] = pbuf[w * 32 + lane];
                const float2 x = *reinterpret_cast<const float2*>(wsum + w * 4 + tq * 2);
                l0 += x.x; l1 += x.y;
            }
            if (epoch1 == 0u && (flags != 0 || head >= RING)) { mbar_wait(bar_epoch, 0); epoch1 = *s_epoch + 1u; }
            const uint32_t tag = (flags & (FLAG_EXTRA | FLAG_FINAL)) ? (epoch1 & 1u) : ring_tag(head);
            float fo0 = 1.f, fo1 = 1.f;
            float* rec = nullptr;
            if (flags & FLAG_FINAL) {
                const float* cg = g_comb + (size_t)head * REC_FLOATS;
                const long long tstart = clock64();
                while ((tag_bad(cO, tag) | tag_bad(cML, tag)) != 0u) {
                    cO  = ld_relaxed_v4(cg + frag);
                    cML = ld_relaxed_v4(cg + SQ * DH + tq * 4);
                    if (clock64() - tstart > SPIN_LIMIT) __trap();
                }
                cO = untag(cO); cML = untag(cML);
                const float M0 = fmaxf(m0, cML.x), M1 = fmaxf(m1, cML.z);
                const float a0 = ex2(m0 - M0), a1 = ex2(m1 - M1), c0 = ex2(cML.x - M0), c1 = ex2(cML.z - M1);
                const float i0 = 1.0f / fmaf(l0, a0, cML.y * c0), i1 = 1.0f / fmaf(l1, a1, cML.w * c1);
                fo0 = a0 * i0; fo1 = a1 * i1;
                cO.x *= c0 * i0; cO.y *= c1 * i1; cO.z *= c0 * i0; cO.w *= c1 * i1;
            } else if (flags & FLAG_EXTRA) {
                rec = g_comb + (size_t)head * REC_FLOATS;
            } else {
                rec = g_ring + ((size_t)(head % RING) * NR + tile) * REC_FLOATS;
                if (head >= RING) {
                    const long long tstart = clock64();
                    while (freeflag != epoch1) {
                        freeflag = ld_relaxed_u32(g_coll + COLL_STRIDE * (head - RING));
                        if (clock64() - tstart > SPIN_LIMIT) __trap();
                    }
                }
            }
            __syncwarp();

            mbar_wait(bar_full + 8 * slot, phase);
            const uint32_t vb = sbase + SM_TILES + slot * TILE_BYTES + vOff;
            uint32_t vf[8][4];
#pragma unroll
            for (int j = 0; j < 8; j++) ldsm_x4_t(vf[j], vb + j * 16 * 128);
            __syncwarp();
            if (lane == 0) mbar_arrive(bar_empty + 8 * slot);
            if (++slot == NSLOTS) { slot = 0; phase ^= 1; }
            float oa[4] = {0.f, 0.f, 0.f, 0.f}, ob[4] = {0.f, 0.f, 0.f, 0.f};
#pragma unroll
            for (int j = 0; j < 8; j += 2) {
                mma_bf16(oa, vf[j], pf[j].x, pf[j].y);
                mma_bf16(ob, vf[j + 1], pf[j + 1].x, pf[j + 1].y);
            }
            if (t < 2) {
                if (flags & FLAG_FINAL) {
                    __nv_bfloat16* op = out + ((size_t)head * SQ + 2 * t) * DH + dcol;
                    op[0]      = __float2bfloat16(fmaf(oa[0] + ob[0], fo0, cO.x));
                    op[DH]     = __float2bfloat16(fmaf(oa[1] + ob[1], fo1, cO.y));
                    op[8]      = __float2bfloat16(fmaf(oa[2] + ob[2], fo0, cO.z));
                    op[DH + 8] = __float2bfloat16(fmaf(oa[3] + ob[3], fo1, cO.w));
                } else {
                    st_relaxed_v4(rec + frag, tagf(oa[0] + ob[0], tag), tagf(oa[1] + ob[1], tag),
                                  tagf(oa[2] + ob[2], tag), tagf(oa[3] + ob[3], tag));
                    if (threadIdx.x < 2) st_relaxed_v4(rec + SQ * DH + t * 4, tagf(m0, tag), tagf(l0, tag), tagf(m1, tag), tagf(l1, tag));
                }
            }
        }
    } else {
        const int e = threadIdx.x - NCW * 32;
        const int half = e >> 7;
        const int f = e & 127;
        const int tq = lane & 1;
        float* cx = reinterpret_cast<float*>(sptr + SM_CX);
        if (e == 0) {
            *s_epoch = ld_relaxed_u32(&g_epoch);
            mbar_arrive(bar_epoch);
        }
        mbar_wait(bar_epoch, 0);
        const uint32_t epoch1 = *s_epoch + 1u;
        const uint32_t etag = epoch1 & 1u;
        for (int k = 0;; k++) {
            const int js = k % JQ; const uint32_t jph = (k / JQ) & 1;
            mbar_wait(bar_jfull + 8 * js, jph);
            const int head = jobq[js];
            __syncwarp();
            if (lane == 0) mbar_arrive(bar_jfree + 8 * js);
            if (head < 0) break;
            const bool deferred = is_deferred(head);
            const uint32_t rtag = ring_tag(head);
            const int nrec_all = deferred ? NR : NR + 1;
            const int r0 = half * HREC;
            const int nrec = (nrec_all - r0 < HREC) ? (nrec_all - r0) : HREC;
            const float* ring = g_ring + ((size_t)(head % RING) * NR + r0) * REC_FLOATS;
            float* comb = g_comb + (size_t)head * REC_FLOATS;
            const int ml_u = lane & 15;
            const bool ml_extra = (r0 + ml_u == NR);
            const float* pml = (ml_extra ? comb : ring + (size_t)ml_u * REC_FLOATS) + SQ * DH + (lane >> 4) * 4;
            const uint32_t mltag = ml_extra ? etag : rtag;
            float4 v[HREC];
#pragma unroll
            for (int u = 0; u < HREC; u++) v[u] = make_float4(0.f, 0.f, 0.f, 0.f);
            float4 pm = make_float4(-INFINITY, 0.f, -INFINITY, 0.f);
            uint32_t pending = (1u << nrec) - 1u;
            const long long tstart = clock64();
            while (true) {
                if ((pending >> ml_u) & 1u) pm = ld_relaxed_v4(pml);
#pragma unroll
                for (int u = 0; u < HREC; u++)
                    if ((pending >> u) & 1u)
                        v[u] = ld_relaxed_v4(((r0 + u == NR) ? comb : ring + (size_t)u * REC_FLOATS) + f * 4);
                uint32_t bad = tag_bad(pm, mltag) << ml_u;
#pragma unroll
                for (int u = 0; u < HREC; u++) bad |= tag_bad(v[u], (r0 + u == NR) ? etag : rtag) << u;
                pending &= __reduce_or_sync(0xffffffffu, bad);
                if (pending == 0u) break;
                if (clock64() - tstart > SPIN_LIMIT) __trap();
                __nanosleep(500);
            }
            pm = untag(pm);
            const bool mlv = ml_u < nrec;
            float Ma = mlv ? pm.x : -INFINITY, Mb = mlv ? pm.z : -INFINITY;
#pragma unroll
            for (int x = 1; x < 16; x <<= 1) {
                Ma = fmaxf(Ma, __shfl_xor_sync(0xffffffffu, Ma, x));
                Mb = fmaxf(Mb, __shfl_xor_sync(0xffffffffu, Mb, x));
            }
            const float sca = mlv ? ex2(pm.x - Ma) : 0.f, scb = mlv ? ex2(pm.z - Mb) : 0.f;
            float La = mlv ? pm.y * sca : 0.f, Lb = mlv ? pm.w * scb : 0.f;
#pragma unroll
            for (int x = 1; x < 16; x <<= 1) {
                La += __shfl_xor_sync(0xffffffffu, La, x);
                Lb += __shfl_xor_sync(0xffffffffu, Lb, x);
            }
            float4 acc = make_float4(0.f, 0.f, 0.f, 0.f);
#pragma unroll
            for (int u = 0; u < HREC; u++) {
                const float sa = __shfl_sync(0xffffffffu, sca, u + 16 * tq), sb = __shfl_sync(0xffffffffu, scb, u + 16 * tq);
                const float4 x = untag(v[u]);
                acc.x = fmaf(x.x, sa, acc.x); acc.y = fmaf(x.y, sb, acc.y);
                acc.z = fmaf(x.z, sa, acc.z); acc.w = fmaf(x.w, sb, acc.w);
            }
            Ma = __shfl_sync(0xffffffffu, Ma, 16 * tq); La = __shfl_sync(0xffffffffu, La, 16 * tq);
            Mb = __shfl_sync(0xffffffffu, Mb, 16 * tq); Lb = __shfl_sync(0xffffffffu, Lb, 16 * tq);
            if (half == 1) {
                *reinterpret_cast<float4*>(cx + f * 4) = acc;
                if (f < 2) *reinterpret_cast<float4*>(cx + SQ * DH + tq * 4) = make_float4(Ma, La, Mb, Lb);
            }
            named_bar_sync(1, NEW * 32);
            if (e == NEW * 32 - 1) st_relaxed_u32(g_coll + COLL_STRIDE * head, epoch1);
            if (half == 0) {
                const float4 ov = *reinterpret_cast<const float4*>(cx + f * 4);
                const float4 oml = *reinterpret_cast<const float4*>(cx + SQ * DH + tq * 4);
                const float M0 = fmaxf(Ma, oml.x), M1 = fmaxf(Mb, oml.z);
                const float fa0 = ex2(Ma - M0), fb0 = ex2(oml.x - M0), fa1 = ex2(Mb - M1), fb1 = ex2(oml.z - M1);
                const float L0 = fmaf(La, fa0, oml.y * fb0), L1 = fmaf(Lb, fa1, oml.w * fb1);
                const float r0x = fmaf(acc.x, fa0, ov.x * fb0), r1x = fmaf(acc.y, fa1, ov.y * fb1);
                const float r0y = fmaf(acc.z, fa0, ov.z * fb0), r1y = fmaf(acc.w, fa1, ov.w * fb1);
                if (deferred) {
                    st_relaxed_v4(comb + f * 4, tagf(r0x, etag), tagf(r1x, etag), tagf(r0y, etag), tagf(r1y, etag));
                    if (f < 2) st_relaxed_v4(comb + SQ * DH + tq * 4, tagf(M0, etag), tagf(L0, etag), tagf(M1, etag), tagf(L1, etag));
                } else {
                    const float i0 = 1.0f / L0, i1 = 1.0f / L1;
                    __nv_bfloat16* op = out + ((size_t)head * SQ + 2 * tq) * DH + (f >> 4) * 16 + ((f >> 1) & 7);
                    op[0]      = __float2bfloat16(r0x * i0);
                    op[DH]     = __float2bfloat16(r1x * i1);
                    op[8]      = __float2bfloat16(r0y * i0);
                    op[DH + 8] = __float2bfloat16(r1y * i1);
                }
            }
            named_bar_sync(1, NEW * 32);
        }
    }
}

typedef CUresult (*EncodeTiledFn)(CUtensorMap*, CUtensorMapDataType, cuuint32_t, void*, const cuuint64_t*,
                                  const cuuint64_t*, const cuuint32_t*, const cuuint32_t*, CUtensorMapInterleave,
                                  CUtensorMapSwizzle, CUtensorMapL2promotion, CUtensorMapFloatOOBfill);

void make_map(EncodeTiledFn enc, CUtensorMap* m, void* p) {
    cuuint64_t dims[2]    = {(cuuint64_t)DH, (cuuint64_t)NHEADS * SKV};
    cuuint64_t strides[1] = {(cuuint64_t)DH * 2};
    cuuint32_t box[2]     = {64, (cuuint32_t)TILE_ROWS};
    cuuint32_t es[2]      = {1, 1};
    enc(m, CU_TENSOR_MAP_DATA_TYPE_BFLOAT16, 2, p, dims, strides, box, es, CU_TENSOR_MAP_INTERLEAVE_NONE,
        CU_TENSOR_MAP_SWIZZLE_128B, CU_TENSOR_MAP_L2_PROMOTION_L2_256B, CU_TENSOR_MAP_FLOAT_OOB_FILL_NONE);
}

}

extern "C" void kernel_launch(void* const* d_in, const int* in_sizes, int n_in, void* d_out, int out_size) {
    (void)in_sizes; (void)n_in; (void)out_size;
    static EncodeTiledFn enc = nullptr;
    static int nsm = 0;
    static unsigned gap_ns = 0;
    if (!enc) {
        cudaDriverEntryPointQueryResult qr;
        void* fn = nullptr;
        cudaGetDriverEntryPoint("cuTensorMapEncodeTiled", &fn, cudaEnableDefault, &qr);
        enc = (EncodeTiledFn)fn;
        cudaFuncSetAttribute(attn_decode_kernel, cudaFuncAttributeMaxDynamicSharedMemorySize, SMEM_BYTES);
        int dev = 0;
        cudaGetDevice(&dev);
        cudaDeviceGetAttribute(&nsm, cudaDevAttrMultiProcessorCount, dev);
        int mem_khz = 0, bus_bits = 0;
        cudaDeviceGetAttribute(&mem_khz, cudaDevAttrMemoryClockRate, dev);
        cudaDeviceGetAttribute(&bus_bits, cudaDevAttrGlobalMemoryBusWidth, dev);
        const double bw = 2.0 * mem_khz * 1e3 * bus_bits / 8.0 * 0.96;
        const int g = nsm < MAX_CTA ? nsm : MAX_CTA;
        double gap = bw > 0.0 ? (double)g * 2.0 * TILE_BYTES / bw * 1e9 - GAP_FIXED_NS : 0.0;
        gap_ns = gap < 0.0 ? 0u : gap > 1200.0 ? 1200u : (unsigned)gap;
    }
    CUtensorMap tmK, tmV, tmQ;
    {
        cuuint64_t dims[2] = {64, (cuuint64_t)NHEADS * SQ * 2}; cuuint64_t strides[1] = {128};
        cuuint32_t box[2] = {64, 8}; cuuint32_t es[2] = {1, 1};
        enc(&tmQ, CU_TENSOR_MAP_DATA_TYPE_BFLOAT16, 2, d_in[0], dims, strides, box, es, CU_TENSOR_MAP_INTERLEAVE_NONE,
            CU_TENSOR_MAP_SWIZZLE_128B, CU_TENSOR_MAP_L2_PROMOTION_NONE, CU_TENSOR_MAP_FLOAT_OOB_FILL_NONE);
    }
    make_map(enc, &tmK, d_in[1]);
    make_map(enc, &tmV, d_in[2]);
    const int grid = nsm < MAX_CTA ? nsm : MAX_CTA;
    attn_decode_kernel<<<grid, NTHREADS, SMEM_BYTES>>>(tmK, tmV, tmQ, (__nv_bfloat16*)d_out, gap_ns);
}
```

```cpp
#include <cuda_runtime.h>
#include <cuda_bf16.h>
#include <cuda.h>
#include <stdint.h>

namespace {

constexpr int NHEADS = 512;
constexpr int SQ     = 4;
constexpr int SKV    = 4096;
constexpr int DH     = 128;

constexpr int TILE_ROWS  = 128;
constexpr int TILE_BYTES = TILE_ROWS * DH * 2;
constexpr int HALF_BYTES = TILE_BYTES / 2;
constexpr int TPH    = SKV / TILE_ROWS;
constexpr int NSLOTS = 4;
constexpr int WIN    = 2;
constexpr int NCW = 8;
constexpr int NEW = 8;
constexpr int NTHREADS = 32 * (NCW + NEW + 1);
constexpr int MAX_CTA = 132;
constexpr double GAP_FIXED_NS = 1600.0;

constexpr int NR   = TPH - 1;
constexpr int TH   = 500;
constexpr int GAP  = 12;
constexpr int HD0  = NHEADS - GAP - TH;
constexpr int NA1  = HD0 * (NR + 1);
constexpr int NA2  = NA1 + TH * NR;
constexpr int NA   = NA2 + GAP * (NR + 1);
constexpr int NCHUNKS = NA + TH;
constexpr int LAG  = 480;
constexpr int LAG_END = 420, HEADS_END = 20;
constexpr int RING = 32;
constexpr int HREC = (NR + 2) / 2;
static_assert(HD0 >= 0 && LAG_END <= TH && LAG <= TH + HEADS_END * NR && LAG < RING * NR && LAG_END < RING * NR &&
              NHEADS % (2 * RING) == 0 && HREC <= 16 && 2 * MAX_CTA <= LAG_END && 2 * MAX_CTA <= RING * NR &&
              WIN + 1 <= NSLOTS, "bad schedule");

constexpr int JQ = 4;
constexpr int REC_BYTES  = SQ * DH * 4 + SQ * 8;
constexpr int REC_FLOATS = 544;

constexpr int SM_TILES = 0;
constexpr int SM_Q     = SM_TILES + NSLOTS * TILE_BYTES;
constexpr int SM_X     = SM_Q + NSLOTS * 1024 - 1024;
constexpr int XS_BYTES = REC_BYTES + 16 + 16;
constexpr int SM_PB    = SM_X + 1024 + NSLOTS * XS_BYTES;
constexpr int SM_WM    = SM_PB + NCW * 32 * 8;
constexpr int SM_WS    = SM_WM + NCW * SQ * 4;
constexpr int SM_CX    = SM_WS + NCW * SQ * 4;
constexpr int SM_META  = SM_CX + REC_BYTES;
constexpr int SM_JOB   = SM_META + NSLOTS * 16;
constexpr int SM_EPOCH = SM_JOB + JQ * 4;
constexpr int SM_BARS  = SM_EPOCH + 16;
constexpr int SM_TOTAL = SM_BARS + (2 * NSLOTS + 2 * JQ + 1) * 8;
constexpr int SMEM_BYTES = SM_TOTAL + 1024;
static_assert(REC_BYTES % 16 == 0 && XS_BYTES % 16 == 0 && SM_BARS % 8 == 0, "align");

constexpr int FLAG_END = 4, FLAG_EXTRA = 8, FLAG_FINAL = 16;

constexpr int COLL_STRIDE = 4;
struct Scratch {
    float ring[(size_t)RING * NR * REC_FLOATS];
    float comb[(size_t)NHEADS * REC_FLOATS];
    unsigned int coll[NHEADS * COLL_STRIDE];
    unsigned int pad0[64];
    unsigned int work;
    unsigned int pad1[63];
    unsigned int done;
    unsigned int pad2[63];
    unsigned int epoch;
};
union ScratchBlob { Scratch s; unsigned char bytes[4 << 20]; };
static_assert(sizeof(Scratch) <= sizeof(ScratchBlob), "scratch");
__device__ __align__(256) ScratchBlob g_scratch;
#define g_ring  (g_scratch.s.ring)
#define g_comb  (g_scratch.s.comb)
#define g_coll  (g_scratch.s.coll)
#define g_work  (g_scratch.s.work)
#define g_done  (g_scratch.s.done)
#define g_epoch (g_scratch.s.epoch)

__device__ __forceinline__ uint32_t smem_u32(const void* p) { return (uint32_t)__cvta_generic_to_shared(p); }
__device__ __forceinline__ void mbar_init(uint32_t bar, uint32_t cnt) {
    asm volatile("mbarrier.init.shared::cta.b64 [%0], %1;" :: "r"(bar), "r"(cnt) : "memory");
}
__device__ __forceinline__ void mbar_expect_tx(uint32_t bar, uint32_t bytes) {
    asm volatile("mbarrier.arrive.expect_tx.shared::cta.b64 _, [%0], %1;" :: "r"(bar), "r"(bytes) : "memory");
}
__device__ __forceinline__ void mbar_arrive(uint32_t bar) {
    asm volatile("mbarrier.arrive.shared::cta.b64 _, [%0];" :: "r"(bar) : "memory");
}
__device__ __forceinline__ bool mbar_try_wait(uint32_t bar, uint32_t parity) {
    uint32_t ok;
    asm volatile("{\n.reg .pred p;\nmbarrier.try_wait.parity.shared::cta.b64 p, [%1], %2;\nselp.u32 %0, 1, 0, p;\n}"
                 : "=r"(ok) : "r"(bar), "r"(parity) : "memory");
    return ok != 0;
}
constexpr long long SPIN_LIMIT = 4000000000LL;
__device__ __forceinline__ void mbar_wait(uint32_t bar, uint32_t parity) {
    if (mbar_try_wait(bar, parity)) return;
    const long long t0 = clock64();
    while (!mbar_try_wait(bar, parity)) {
        if (clock64() - t0 > SPIN_LIMIT) __trap();
    }
}
__device__ __forceinline__ void tma_load_2d(uint32_t dst, const CUtensorMap* tm, int c0, int c1, uint32_t bar, uint64_t pol) {
    asm volatile("cp.async.bulk.tensor.2d.shared::cluster.global.mbarrier::complete_tx::bytes.L2::cache_hint [%0], [%1, {%3, %4}], [%2], %5;"
                 :: "r"(dst), "l"(tm), "r"(bar), "r"(c0), "r"(c1), "l"(pol) : "memory");
}
__device__ __forceinline__ void tma_load_2d_nh(uint32_t dst, const CUtensorMap* tm, int c0, int c1, uint32_t bar) {
    asm volatile("cp.async.bulk.tensor.2d.shared::cluster.global.mbarrier::complete_tx::bytes [%0], [%1, {%3, %4}], [%2];"
                 :: "r"(dst), "l"(tm), "r"(bar), "r"(c0), "r"(c1) : "memory");
}
__device__ __forceinline__ void bulk_load(uint32_t dst, const void* src, uint32_t bytes, uint32_t bar) {
    asm volatile("cp.async.bulk.shared::cluster.global.mbarrier::complete_tx::bytes [%0], [%1], %2, [%3];"
                 :: "r"(dst), "l"(src), "r"(bytes), "r"(bar) : "memory");
}
__device__ __forceinline__ void ldsm_x4(uint32_t (&r)[4], uint32_t addr) {
    asm volatile("ldmatrix.sync.aligned.m8n8.x4.shared.b16 {%0,%1,%2,%3}, [%4];"
                 : "=r"(r[0]), "=r"(r[1]), "=r"(r[2]), "=r"(r[3]) : "r"(addr) : "memory");
}
__device__ __forceinline__ void ldsm_x4_t(uint32_t (&r)[4], uint32_t addr) {
    asm volatile("ldmatrix.sync.aligned.m8n8.x4.trans.shared.b16 {%0,%1,%2,%3}, [%4];"
                 : "=r"(r[0]), "=r"(r[1]), "=r"(r[2]), "=r"(r[3]) : "r"(addr) : "memory");
}
__device__ __forceinline__ void mma_bf16(float (&d)[4], const uint32_t (&a)[4], uint32_t b0, uint32_t b1) {
    asm volatile("mma.sync.aligned.m16n8k16.row.col.f32.bf16.bf16.f32 {%0,%1,%2,%3}, {%4,%5,%6,%7}, {%8,%9}, {%0,%1,%2,%3};"
                 : "+f"(d[0]), "+f"(d[1]), "+f"(d[2]), "+f"(d[3])
                 : "r"(a[0]), "r"(a[1]), "r"(a[2]), "r"(a[3]), "r"(b0), "r"(b1));
}
__device__ __forceinline__ uint32_t movmatrix_t(uint32_t a) {
    uint32_t d;
    asm volatile("movmatrix.sync.aligned.m8n8.trans.b16 %0, %1;" : "=r"(d) : "r"(a));
    return d;
}
__device__ __forceinline__ uint32_t pack_bf16(float lo, float hi) {
    uint32_t d;
    asm("cvt.rn.bf16x2.f32 %0, %1, %2;" : "=r"(d) : "f"(hi), "f"(lo));
    return d;
}
__device__ __forceinline__ float ex2(float x) {
    float y;
    asm("ex2.approx.ftz.f32 %0, %1;" : "=f"(y) : "f"(x));
    return y;
}
__device__ __forceinline__ void named_bar_sync(int id, int nthreads) {
    asm volatile("bar.sync %0, %1;" :: "r"(id), "r"(nthreads) : "memory");
}
__device__ __forceinline__ unsigned atom_inc_relaxed(unsigned int* p) {
    unsigned o;
    asm volatile("atom.relaxed.gpu.global.add.u32 %0, [%1], 1;" : "=r"(o) : "l"(p) : "memory");
    return o;
}
__device__ __forceinline__ unsigned long long global_ns() {
    unsigned long long t;
    asm volatile("mov.u64 %0, %globaltimer;" : "=l"(t));
    return t;
}
__device__ __forceinline__ uint32_t fbits(float x) { return __float_as_uint(x); }
__device__ __forceinline__ float tagf(float x, uint32_t tag) { return __uint_as_float((fbits(x) & ~1u) | tag); }
__device__ __forceinline__ float4 untag(const float4& v) {
    return make_float4(tagf(v.x, 0u), tagf(v.y, 0u), tagf(v.z, 0u), tagf(v.w, 0u));
}
__device__ __forceinline__ uint32_t tag_bad(const float4& v, uint32_t tag) {
    return ((fbits(v.x) ^ tag) | (fbits(v.y) ^ tag) | (fbits(v.z) ^ tag) | (fbits(v.w) ^ tag)) & 1u;
}
__device__ __forceinline__ void st_relaxed_u32(unsigned int* p, uint32_t x) {
    asm volatile("st.relaxed.gpu.global.u32 [%0], %1;" :: "l"(p), "r"(x) : "memory");
}
__device__ __forceinline__ void st_relaxed_v4(float* p, float x, float y, float z, float w) {
    asm volatile("st.relaxed.gpu.global.v4.f32 [%0], {%1, %2, %3, %4};" :: "l"(p), "f"(x), "f"(y), "f"(z), "f"(w) : "memory");
}
__device__ __forceinline__ uint32_t ld_relaxed_u32(const unsigned int* p) {
    uint32_t v;
    asm volatile("ld.relaxed.gpu.global.u32 %0, [%1];" : "=r"(v) : "l"(p) : "memory");
    return v;
}
__device__ __forceinline__ float4 ld_relaxed_v4(const float* p) {
    float4 v;
    asm volatile("ld.relaxed.gpu.global.v4.f32 {%0,%1,%2,%3}, [%4];" : "=f"(v.x), "=f"(v.y), "=f"(v.z), "=f"(v.w) : "l"(p) : "memory");
    return v;
}

__device__ __forceinline__ void decode_a(int c, int& head, int& tile, int& cnt) {
    if (c < NA1)      { cnt = NR + 1; head = c / (NR + 1); tile = c % (NR + 1); }
    else if (c < NA2) { cnt = NR;     head = HD0 + (c - NA1) / NR; tile = (c - NA1) % NR; }
    else              { cnt = NR + 1; head = HD0 + TH + (c - NA2) / (NR + 1); tile = (c - NA2) % (NR + 1); }
}
__device__ __forceinline__ bool is_deferred(int head) { return head >= HD0 && head < HD0 + TH; }
__device__ __forceinline__ uint32_t ring_tag(int head) { return (uint32_t)(head / RING + 1) & 1u; }

__global__ void __launch_bounds__(NTHREADS, 1)
attn_decode_kernel(const __grid_constant__ CUtensorMap tmK, const __grid_constant__ CUtensorMap tmV,
                   const __grid_constant__ CUtensorMap tmQ, __nv_bfloat16* __restrict__ out, const unsigned gap_ns)
{
    extern __shared__ unsigned char smem_raw[];
    const uint32_t sbase = (smem_u32(smem_raw) + 1023u) & ~1023u;
    unsigned char* sptr = smem_raw + (sbase - smem_u32(smem_raw));

    const int warp = threadIdx.x >> 5, lane = threadIdx.x & 31;
    const uint32_t bar_full  = sbase + SM_BARS;
    const uint32_t bar_empty = bar_full + NSLOTS * 8;
    const uint32_t bar_jfull = bar_empty + NSLOTS * 8;
    const uint32_t bar_jfree = bar_jfull + JQ * 8;
    const uint32_t bar_epoch = bar_jfree + JQ * 8;
    volatile uint32_t* s_epoch = reinterpret_cast<volatile uint32_t*>(sptr + SM_EPOCH);
    volatile int4* meta = reinterpret_cast<volatile int4*>(sptr + SM_META);
    volatile int* jobq = reinterpret_cast<volatile int*>(sptr + SM_JOB);

    uint64_t pol = 0;
    if (threadIdx.x == NTHREADS - 32) {
        mbar_init(bar_full, 1);
        mbar_init(bar_full + 8, 1);
        asm volatile("fence.mbarrier_init.release.cluster;" ::: "memory");
        asm volatile("createpolicy.fractional.L2::evict_first.b64 %0, 1.0;" : "=l"(pol));
        int head, tile, cnt;
        decode_a((int)blockIdx.x, head, tile, cnt);
        const int row = head * SKV + tile * TILE_ROWS;
        meta[0].x = head; meta[0].y = tile; meta[0].w = (tile == NR) ? FLAG_EXTRA : 0;
        mbar_expect_tx(bar_full, TILE_BYTES + SQ * DH * 2);
        tma_load_2d(sbase + SM_TILES, &tmK, 0, row, bar_full, pol);
        tma_load_2d(sbase + SM_TILES + HALF_BYTES, &tmK, 64, row, bar_full, pol);
        mbar_expect_tx(bar_full + 8, TILE_BYTES);
        tma_load_2d(sbase + SM_TILES + TILE_BYTES, &tmV, 0, row, bar_full + 8, pol);
        tma_load_2d(sbase + SM_TILES + TILE_BYTES + HALF_BYTES, &tmV, 64, row, bar_full + 8, pol);
        tma_load_2d_nh(sbase + SM_Q, &tmQ, 0, head * 8, bar_full);
        for (int s = 2; s < NSLOTS; s++) mbar_init(bar_full + 8 * s, 1);
        for (int s = 0; s < NSLOTS; s++) mbar_init(bar_empty + 8 * s, NCW);
        for (int s = 0; s < JQ; s++) { mbar_init(bar_jfull + 8 * s, 1); mbar_init(bar_jfree + 8 * s, NEW); }
        mbar_init(bar_epoch, 1);
        asm volatile("fence.mbarrier_init.release.cluster;" ::: "memory");
    }
    __syncthreads();

    const float SC = 0.08838834764831845f * 1.4426950408889634f;

    if (warp == NCW + NEW) {
        if (lane == 0) {
            int nissued = 2;
            int job = 0;
            unsigned c = blockIdx.x + gridDim.x;
            while (c < (unsigned)NCHUNKS) {
                int head, tile, kind = 0;
                if (c < (unsigned)NA) {
                    int cnt;
                    decode_a((int)c, head, tile, cnt);
                    if (tile == NR) kind = FLAG_EXTRA;
                } else {
                    head = HD0 + ((int)c - NA); tile = NR; kind = FLAG_FINAL;
                }
#pragma unroll
                for (int z = 0; z < 2; z++) {
                    const int cc = (int)c - (z == 0 ? LAG : LAG_END);
                    if (cc >= 0 && cc < NA) {
                        int h2, t2, cnt2;
                        decode_a(cc, h2, t2, cnt2);
                        if (t2 == cnt2 - 1 && ((h2 >= NHEADS - HEADS_END) == (z == 1))) {
                            const int js = job % JQ;
                            mbar_wait(bar_jfree + 8 * js, ((job / JQ) & 1) ^ 1);
                            jobq[js] = h2;
                            mbar_arrive(bar_jfull + 8 * js);
                            job++;
                        }
                    }
                }
                const bool chk = (kind == 0) && head >= RING;
                const int row = head * SKV + tile * TILE_ROWS;
                unsigned long long tk = 0;
#pragma unroll
                for (int i = 0; i < 2; i++) {
                    const int slot = nissued % NSLOTS;
                    if (nissued > WIN) {
                        const int prev = nissued - WIN;
                        mbar_wait(bar_full + 8 * (prev % NSLOTS), (prev / NSLOTS) & 1);
                    }
                    mbar_wait(bar_empty + 8 * slot, ((nissued / NSLOTS) & 1) ^ 1);
                    const uint32_t fb = bar_full + 8 * slot, dst = sbase + SM_TILES + slot * TILE_BYTES;
                    if (i == 0) {
                        const uint32_t xb = sbase + SM_X + slot * XS_BYTES;
                        meta[slot].x = head; meta[slot].y = tile; meta[slot].w = kind;
                        mbar_expect_tx(fb, TILE_BYTES + SQ * DH * 2 + (kind == FLAG_FINAL ? REC_BYTES : 0) + (chk ? 16 : 0));
                        tma_load_2d(dst, &tmK, 0, row, fb, pol);
                        tma_load_2d(dst + HALF_BYTES, &tmK, 64, row, fb, pol);
                        tma_load_2d_nh(sbase + SM_Q + slot * 1024, &tmQ, 0, head * 8, fb);
                        if (kind == FLAG_FINAL) bulk_load(xb + 1024, g_comb + (size_t)head * REC_FLOATS, REC_BYTES, fb);
                        if (chk) bulk_load(xb + 1024 + REC_BYTES, g_coll + COLL_STRIDE * (head - RING), 16, fb);
                        tk = global_ns();
                    } else {
                        while (global_ns() - tk < gap_ns) {}
                        mbar_expect_tx(fb, TILE_BYTES);
                        tma_load_2d(dst, &tmV, 0, row, fb, pol);
                        tma_load_2d(dst + HALF_BYTES, &tmV, 64, row, fb, pol);
                    }
                    nissued++;
                }
                c = atom_inc_relaxed(&g_work) + 2 * gridDim.x;
            }
            {
                const int js = job % JQ;
                mbar_wait(bar_jfree + 8 * js, ((job / JQ) & 1) ^ 1);
                jobq[js] = -1;
                mbar_arrive(bar_jfull + 8 * js);
            }
            {
                const int slot = nissued % NSLOTS;
                mbar_wait(bar_empty + 8 * slot, ((nissued / NSLOTS) & 1) ^ 1);
                meta[slot].w = FLAG_END;
                mbar_arrive(bar_full + 8 * slot);
            }
            mbar_wait(bar_epoch, 0);
            if (atom_inc_relaxed(&g_done) == gridDim.x - 1) { g_work = 0; g_done = 0; g_epoch = *s_epoch + 1u; }
        }
    } else if (warp < NCW) {
        const int g = lane >> 2, t = lane & 3, r8 = lane & 7;
        const uint32_t kOff = (uint32_t)((warp * 16 + r8 + ((lane >> 3) & 1) * 8) * 128 + (((lane >> 4) ^ r8) << 4));
        const uint32_t vOff = (uint32_t)((warp >> 2) * HALF_BYTES + (r8 + (lane >> 4) * 8) * 128 +
                                         (((((2 * warp) & 7) | ((lane >> 3) & 1)) ^ r8) << 4));
        float* wmax = reinterpret_cast<float*>(sptr + SM_WM);
        float* wsum = reinterpret_cast<float*>(sptr + SM_WS);
        uint2* pbuf = reinterpret_cast<uint2*>(sptr + SM_PB);
        const int tq = t & 1;
        const int dcol = warp * 16 + g;
        const int frag = (warp * 16 + g * 2 + tq) * 4;
        int slot = 0; uint32_t phase = 0;
        uint32_t epoch1 = 0u;
        while (true) {
            mbar_wait(bar_full + 8 * slot, phase);
            const int flags = meta[slot].w;
            if (flags & FLAG_END) break;
            const int head = meta[slot].x, tile = meta[slot].y;
            const uint32_t kb = sbase + SM_TILES + slot * TILE_BYTES;
            const unsigned char* xs = sptr + SM_X + slot * XS_BYTES;
            uint32_t kf[8][4];
#pragma unroll
            for (int j = 0; j < 8; j++)
                ldsm_x4(kf[j], kb + (j >> 2) * HALF_BYTES + (kOff ^ (uint32_t)(((2 * j) & 7) << 4)));
            uint32_t qf[4][4];
#pragma unroll
            for (int i = 0; i < 4; i++) {
                const int hr = 2 * (lane & 3) + (i >> 1);
                const int cc = ((i & 1) * 4 + (lane >> 3));
                ldsm_x4(qf[i], sbase + SM_Q + slot * 1024 + hr * 128 + ((cc ^ hr) << 4));
            }
            float4 cO = make_float4(0.f, 0.f, 0.f, 0.f), cML = make_float4(0.f, 0.f, 0.f, 0.f);
            if (flags & FLAG_FINAL) {
                const float* cs = reinterpret_cast<const float*>(xs + 1024);
                cO  = *reinterpret_cast<const float4*>(cs + frag);
                cML = *reinterpret_cast<const float4*>(cs + SQ * DH + tq * 4);
            }
            uint32_t freeflag = *reinterpret_cast<const uint32_t*>(xs + 1024 + REC_BYTES);
            __syncwarp();
            if (lane == 0) mbar_arrive(bar_empty + 8 * slot);
            if (++slot == NSLOTS) { slot = 0; phase ^= 1; }

            float sa[4] = {0.f, 0.f, 0.f, 0.f}, sb[4] = {0.f, 0.f, 0.f, 0.f};
#pragma unroll
            for (int j = 0; j < 8; j += 2) {
                mma_bf16(sa, kf[j], qf[j >> 1][0], qf[j >> 1][1]);
                mma_bf16(sb, kf[j + 1], qf[j >> 1][2], qf[j >> 1][3]);
            }
            const float s0 = sa[0] + sb[0], s1 = sa[1] + sb[1], s2 = sa[2] + sb[2], s3 = sa[3] + sb[3];
            float t0 = fmaxf(s0, s2), t1 = fmaxf(s1, s3);
#pragma unroll
            for (int x = 4; x <= 16; x <<= 1) {
                t0 = fmaxf(t0, __shfl_xor_sync(0xffffffffu, t0, x));
                t1 = fmaxf(t1, __shfl_xor_sync(0xffffffffu, t1, x));
            }
            if (lane < 2) *reinterpret_cast<float2*>(wmax + lane * 16 + warp * 2) = make_float2(t0, t1);
            named_bar_sync(2, NCW * 32);
            float m0 = -INFINITY, m1 = -INFINITY;
#pragma unroll
            for (int w = 0; w < NCW / 2; w++) {
                const float4 x = *reinterpret_cast<const float4*>(wmax + tq * 16 + w * 4);
                m0 = fmaxf(m0, fmaxf(x.x, x.z)); m1 = fmaxf(m1, fmaxf(x.y, x.w));
            }
            m0 = tagf(m0 * SC, 0u); m1 = tagf(m1 * SC, 0u);
            float p0 = ex2(fmaf(s0, SC, -m0)), p1 = ex2(fmaf(s1, SC, -m1));
            float p2 = ex2(fmaf(s2, SC, -m0)), p3 = ex2(fmaf(s3, SC, -m1));
            if (t >= 2) { p0 = p1 = p2 = p3 = 0.f; }
            {
                uint2 bb;
                bb.x = movmatrix_t(pack_bf16(p0, p1));
                bb.y = movmatrix_t(pack_bf16(p2, p3));
                if (lane < 16) pbuf[(warp >> 1) * 32 + lane * 2 + (warp & 1)] = bb;
                float r0 = p0 + p2, r1 = p1 + p3;
#pragma unroll
                for (int x = 4; x <= 16; x <<= 1) {
                    r0 += __shfl_xor_sync(0xffffffffu, r0, x);
                    r1 += __shfl_xor_sync(0xffffffffu, r1, x);
                }
                if (lane < 2) *reinterpret_cast<float2*>(wsum + lane * 16 + warp * 2) = make_float2(r0, r1);
            }
            named_bar_sync(2, NCW * 32);
            uint2 pf[8];
            float l0 = 0.f, l1 = 0.f;
#pragma unroll
            for (int w = 0; w < NCW / 2; w++) {
                const uint4 y = *reinterpret_cast<const uint4*>(pbuf + w * 32 + (lane & 15) * 2);
                pf[2 * w] = make_uint2(y.x, y.y); pf[2 * w + 1] = make_uint2(y.z, y.w);
                const float4 x = *reinterpret_cast<const float4*>(wsum + tq * 16 + w * 4);
                l0 += x.x; l1 += x.y; l0 += x.z; l1 += x.w;
            }
            if (epoch1 == 0u && (flags != 0 || head >= RING)) { mbar_wait(bar_epoch, 0); epoch1 = *s_epoch + 1u; }
            const uint32_t tag = (flags & (FLAG_EXTRA | FLAG_FINAL)) ? (epoch1 & 1u) : ring_tag(head);
            float fo0 = 1.f, fo1 = 1.f;
            float* rec = nullptr;
            if (flags & FLAG_FINAL) {
                const float* cg = g_comb + (size_t)head * REC_FLOATS;
                const long long tstart = clock64();
                while ((tag_bad(cO, tag) | tag_bad(cML, tag)) != 0u) {
                    cO  = ld_relaxed_v4(cg + frag);
                    cML = ld_relaxed_v4(cg + SQ * DH + tq * 4);
                    if (clock64() - tstart > SPIN_LIMIT) __trap();
                }
                cO = untag(cO); cML = untag(cML);
                const float M0 = fmaxf(m0, cML.x), M1 = fmaxf(m1, cML.z);
                const float a0 = ex2(m0 - M0), a1 = ex2(m1 - M1), c0 = ex2(cML.x - M0), c1 = ex2(cML.z - M1);
                const float i0 = 1.0f / fmaf(l0, a0, cML.y * c0), i1 = 1.0f / fmaf(l1, a1, cML.w * c1);
                fo0 = a0 * i0; fo1 = a1 * i1;
                cO.x *= c0 * i0; cO.y *= c1 * i1; cO.z *= c0 * i0; cO.w *= c1 * i1;
            } else if (flags & FLAG_EXTRA) {
                rec = g_comb + (size_t)head * REC_FLOATS;
            } else {
                rec = g_ring + ((size_t)(head % RING) * NR + tile) * REC_FLOATS;
                if (head >= RING) {
                    const long long tstart = clock64();
                    while (freeflag != epoch1) {
                        freeflag = ld_relaxed_u32(g_coll + COLL_STRIDE * (head - RING));
                        if (clock64() - tstart > SPIN_LIMIT) __trap();
                    }
                }
            }
            __syncwarp();

            mbar_wait(bar_full + 8 * slot, phase);
            const uint32_t vb = sbase + SM_TILES + slot * TILE_BYTES + vOff;
            uint32_t vf[8][4];
#pragma unroll
            for (int j = 0; j < 8; j++) ldsm_x4_t(vf[j], vb + j * 16 * 128);
            __syncwarp();
            if (lane == 0) mbar_arrive(bar_empty + 8 * slot);
            if (++slot == NSLOTS) { slot = 0; phase ^= 1; }
            float oa[4] = {0.f, 0.f, 0.f, 0.f}, ob[4] = {0.f, 0.f, 0.f, 0.f};
#pragma unroll
            for (int j = 0; j < 8; j += 2) {
                mma_bf16(oa, vf[j], pf[j].x, pf[j].y);
                mma_bf16(ob, vf[j + 1], pf[j + 1].x, pf[j + 1].y);
            }
            if (t < 2) {
                if (flags & FLAG_FINAL) {
                    __nv_bfloat16* op = out + ((size_t)head * SQ + 2 * t) * DH + dcol;
                    op[0]      = __float2bfloat16(fmaf(oa[0] + ob[0], fo0, cO.x));
                    op[DH]     = __float2bfloat16(fmaf(oa[1] + ob[1], fo1, cO.y));
                    op[8]      = __float2bfloat16(fmaf(oa[2] + ob[2], fo0, cO.z));
                    op[DH + 8] = __float2bfloat16(fmaf(oa[3] + ob[3], fo1, cO.w));
                } else {
                    st_relaxed_v4(rec + frag, tagf(oa[0] + ob[0], tag), tagf(oa[1] + ob[1], tag),
                                  tagf(oa[2] + ob[2], tag), tagf(oa[3] + ob[3], tag));
                    if (threadIdx.x < 2) st_relaxed_v4(rec + SQ * DH + t * 4, tagf(m0, tag), tagf(l0, tag), tagf(m1, tag), tagf(l1, tag));
                }
            }
        }
    } else {
        const int e = threadIdx.x - NCW * 32;
        const int half = e >> 7;
        const int f = e & 127;
        const int tq = lane & 1;
        float* cx = reinterpret_cast<float*>(sptr + SM_CX);
        if (e == 0) {
            *s_epoch = ld_relaxed_u32(&g_epoch);
            mbar_arrive(bar_epoch);
        }
        mbar_wait(bar_epoch, 0);
        const uint32_t epoch1 = *s_epoch + 1u;
        const uint32_t etag = epoch1 & 1u;
        for (int k = 0;; k++) {
            const int js = k % JQ; const uint32_t jph = (k / JQ) & 1;
            mbar_wait(bar_jfull + 8 * js, jph);
            const int head = jobq[js];
            __syncwarp();
            if (lane == 0) mbar_arrive(bar_jfree + 8 * js);
            if (head < 0) break;
            const bool deferred = is_deferred(head);
            const uint32_t rtag = ring_tag(head);
            const int nrec_all = deferred ? NR : NR + 1;
            const int r0 = half * HREC;
            const int nrec = (nrec_all - r0 < HREC) ? (nrec_all - r0) : HREC;
            const float* ring = g_ring + ((size_t)(head % RING) * NR + r0) * REC_FLOATS;
            float* comb = g_comb + (size_t)head * REC_FLOATS;
            const int ml_u = lane & 15;
            const bool ml_extra = (r0 + ml_u == NR);
            const float* pml = (ml_extra ? comb : ring + (size_t)ml_u * REC_FLOATS) + SQ * DH + (lane >> 4) * 4;
            const uint32_t mltag = ml_extra ? etag : rtag;
            float4 v[HREC];
#pragma unroll
            for (int u = 0; u < HREC; u++) v[u] = make_float4(0.f, 0.f, 0.f, 0.f);
            float4 pm = make_float4(-INFINITY, 0.f, -INFINITY, 0.f);
            uint32_t pending = (1u << nrec) - 1u;
            const long long tstart = clock64();
            while (true) {
                if ((pending >> ml_u) & 1u) pm = ld_relaxed_v4(pml);
#pragma unroll
                for (int u = 0; u < HREC; u++)
                    if ((pending >> u) & 1u)
                        v[u] = ld_relaxed_v4(((r0 + u == NR) ? comb : ring + (size_t)u * REC_FLOATS) + f * 4);
                uint32_t bad = tag_bad(pm, mltag) << ml_u;
#pragma unroll
                for (int u = 0; u < HREC; u++) bad |= tag_bad(v[u], (r0 + u == NR) ? etag : rtag) << u;
                pending &= __reduce_or_sync(0xffffffffu, bad);
                if (pending == 0u) break;
                if (clock64() - tstart > SPIN_LIMIT) __trap();
                __nanosleep(500);
            }
            pm = untag(pm);
            const bool mlv = ml_u < nrec;
            float Ma = mlv ? pm.x : -INFINITY, Mb = mlv ? pm.z : -INFINITY;
#pragma unroll
            for (int x = 1; x < 16; x <<= 1) {
                Ma = fmaxf(Ma, __shfl_xor_sync(0xffffffffu, Ma, x));
                Mb = fmaxf(Mb, __shfl_xor_sync(0xffffffffu, Mb, x));
            }
            const float sca = mlv ? ex2(pm.x - Ma) : 0.f, scb = mlv ? ex2(pm.z - Mb) : 0.f;
            float La = mlv ? pm.y * sca : 0.f, Lb = mlv ? pm.w * scb : 0.f;
#pragma unroll
            for (int x = 1; x < 16; x <<= 1) {
                La += __shfl_xor_sync(0xffffffffu, La, x);
                Lb += __shfl_xor_sync(0xffffffffu, Lb, x);
            }
            float4 acc = make_float4(0.f, 0.f, 0.f, 0.f);
#pragma unroll
            for (int u = 0; u < HREC; u++) {
                const float sa = __shfl_sync(0xffffffffu, sca, u + 16 * tq), sb = __shfl_sync(0xffffffffu, scb, u + 16 * tq);
                const float4 x = untag(v[u]);
                acc.x = fmaf(x.x, sa, acc.x); acc.y = fmaf(x.y, sb, acc.y);
                acc.z = fmaf(x.z, sa, acc.z); acc.w = fmaf(x.w, sb, acc.w);
            }
            Ma = __shfl_sync(0xffffffffu, Ma, 16 * tq); La = __shfl_sync(0xffffffffu, La, 16 * tq);
            Mb = __shfl_sync(0xffffffffu, Mb, 16 * tq); Lb = __shfl_sync(0xffffffffu, Lb, 16 * tq);
            if (half == 1) {
                *reinterpret_cast<float4*>(cx + f * 4) = acc;
                if (f < 2) *reinterpret_cast<float4*>(cx + SQ * DH + tq * 4) = make_float4(Ma, La, Mb, Lb);
            }
            named_bar_sync(1, NEW * 32);
            if (e == NEW * 32 - 1) st_relaxed_u32(g_coll + COLL_STRIDE * head, epoch1);
            if (half == 0) {
                const float4 ov = *reinterpret_cast<const float4*>(cx + f * 4);
                const float4 oml = *reinterpret_cast<const float4*>(cx + SQ * DH + tq * 4);
                const float M0 = fmaxf(Ma, oml.x), M1 = fmaxf(Mb, oml.z);
                const float fa0 = ex2(Ma - M0), fb0 = ex2(oml.x - M0), fa1 = ex2(Mb - M1), fb1 = ex2(oml.z - M1);
                const float L0 = fmaf(La, fa0, oml.y * fb0), L1 = fmaf(Lb, fa1, oml.w * fb1);
                const float r0x = fmaf(acc.x, fa0, ov.x * fb0), r1x = fmaf(acc.y, fa1, ov.y * fb1);
                const float r0y = fmaf(acc.z, fa0, ov.z * fb0), r1y = fmaf(acc.w, fa1, ov.w * fb1);
                if (deferred) {
                    st_relaxed_v4(comb + f * 4, tagf(r0x, etag), tagf(r1x, etag), tagf(r0y, etag), tagf(r1y, etag));
                    if (f < 2) st_relaxed_v4(comb + SQ * DH + tq * 4, tagf(M0, etag), tagf(L0, etag), tagf(M1, etag), tagf(L1, etag));
                } else {
                    const float i0 = 1.0f / L0, i1 = 1.0f / L1;
                    __nv_bfloat16* op = out + ((size_t)head * SQ + 2 * tq) * DH + (f >> 4) * 16 + ((f >> 1) & 7);
                    op[0]      = __float2bfloat16(r0x * i0);
                    op[DH]     = __float2bfloat16(r1x * i1);
                    op[8]      = __float2bfloat16(r0y * i0);
                    op[DH + 8] = __float2bfloat16(r1y * i1);
                }
            }
            named_bar_sync(1, NEW * 32);
        }
    }
}

typedef CUresult (*EncodeTiledFn)(CUtensorMap*, CUtensorMapDataType, cuuint32_t, void*, const cuuint64_t*,
                                  const cuuint64_t*, const cuuint32_t*, const cuuint32_t*, CUtensorMapInterleave,
                                  CUtensorMapSwizzle, CUtensorMapL2promotion, CUtensorMapFloatOOBfill);

void make_map(EncodeTiledFn enc, CUtensorMap* m, void* p) {
    cuuint64_t dims[2]    = {(cuuint64_t)DH, (cuuint64_t)NHEADS * SKV};
    cuuint64_t strides[1] = {(cuuint64_t)DH * 2};
    cuuint32_t box[2]     = {64, (cuuint32_t)TILE_ROWS};
    cuuint32_t es[2]      = {1, 1};
    enc(m, CU_TENSOR_MAP_DATA_TYPE_BFLOAT16, 2, p, dims, strides, box, es, CU_TENSOR_MAP_INTERLEAVE_NONE,
        CU_TENSOR_MAP_SWIZZLE_128B, CU_TENSOR_MAP_L2_PROMOTION_L2_256B, CU_TENSOR_MAP_FLOAT_OOB_FILL_NONE);
}

}

extern "C" void kernel_launch(void* const* d_in, const int* in_sizes, int n_in, void* d_out, int out_size) {
    (void)in_sizes; (void)n_in; (void)out_size;
    static EncodeTiledFn enc = nullptr;
    static int nsm = 0;
    static unsigned gap_ns = 0;
    if (!enc) {
        cudaDriverEntryPointQueryResult qr;
        void* fn = nullptr;
        cudaGetDriverEntryPoint("cuTensorMapEncodeTiled", &fn, cudaEnableDefault, &qr);
        enc = (EncodeTiledFn)fn;
        cudaFuncSetAttribute(attn_decode_kernel, cudaFuncAttributeMaxDynamicSharedMemorySize, SMEM_BYTES);
        int dev = 0;
        cudaGetDevice(&dev);
        cudaDeviceGetAttribute(&nsm, cudaDevAttrMultiProcessorCount, dev);
        int mem_khz = 0, bus_bits = 0;
        cudaDeviceGetAttribute(&mem_khz, cudaDevAttrMemoryClockRate, dev);
        cudaDeviceGetAttribute(&bus_bits, cudaDevAttrGlobalMemoryBusWidth, dev);
        const double bw = 2.0 * mem_khz * 1e3 * bus_bits / 8.0 * 0.96;
        const int g = nsm < MAX_CTA ? nsm : MAX_CTA;
        double gap = bw > 0.0 ? (double)g * 2.0 * TILE_BYTES / bw * 1e9 - GAP_FIXED_NS : 0.0;
        gap_ns = gap < 0.0 ? 0u : gap > 1200.0 ? 1200u : (unsigned)gap;
    }
    CUtensorMap tmK, tmV, tmQ;
    {
        cuuint64_t dims[2] = {64, (cuuint64_t)NHEADS * SQ * 2}; cuuint64_t strides[1] = {128};
        cuuint32_t box[2] = {64, 8}; cuuint32_t es[2] = {1, 1};
        enc(&tmQ, CU_TENSOR_MAP_DATA_TYPE_BFLOAT16, 2, d_in[0], dims, strides, box, es, CU_TENSOR_MAP_INTERLEAVE_NONE,
            CU_TENSOR_MAP_SWIZZLE_128B, CU_TENSOR_MAP_L2_PROMOTION_NONE, CU_TENSOR_MAP_FLOAT_OOB_FILL_NONE);
    }
    make_map(enc, &tmK, d_in[1]);
    make_map(enc, &tmV, d_in[2]);
    const int grid = nsm < MAX_CTA ? nsm : MAX_CTA;
    attn_decode_kernel<<<grid, NTHREADS, SMEM_BYTES>>>(tmK, tmV, tmQ, (__nv_bfloat16*)d_out, gap_ns);
}
```

```cpp
#include <cuda_runtime.h>
#include <cuda_bf16.h>
#include <cuda.h>
#include <stdint.h>

namespace {

constexpr int NHEADS = 512;
constexpr int SQ     = 4;
constexpr int SKV    = 4096;
constexpr int DH     = 128;

constexpr int TILE_ROWS  = 128;
constexpr int TILE_BYTES = TILE_ROWS * DH * 2;
constexpr int HALF_BYTES = TILE_BYTES / 2;
constexpr int TPH    = SKV / TILE_ROWS;
constexpr int NSLOTS = 4;
constexpr int WIN    = 2;
constexpr int NCW = 8;
constexpr int NEW = 8;
constexpr int NTHREADS = 32 * (NCW + NEW + 1);
constexpr int MAX_CTA = 132;
constexpr double GAP_FIXED_NS = 1600.0;

constexpr int NR   = TPH - 1;
constexpr int TH   = 500;
constexpr int GAP  = 12;
constexpr int HD0  = NHEADS - GAP - TH;
constexpr int NA1  = HD0 * (NR + 1);
constexpr int NA2  = NA1 + TH * NR;
constexpr int NA   = NA2 + GAP * (NR + 1);
constexpr int NCHUNKS = NA + TH;
constexpr int LAG  = 480;
constexpr int LAG_END = 420, HEADS_END = 20;
constexpr int RING = 32;
constexpr int HREC = (NR + 2) / 2;
static_assert(HD0 >= 0 && LAG_END <= TH && LAG <= TH + HEADS_END * NR && LAG < RING * NR && LAG_END < RING * NR &&
              NHEADS % (2 * RING) == 0 && HREC <= 16 && 2 * MAX_CTA <= LAG_END && 2 * MAX_CTA <= RING * NR &&
              WIN + 1 <= NSLOTS, "bad schedule");

constexpr int JQ = 4;
constexpr int REC_BYTES  = SQ * DH * 4 + SQ * 8;
constexpr int REC_FLOATS = 544;

constexpr int SM_TILES = 0;
constexpr int SM_Q     = SM_TILES + NSLOTS * TILE_BYTES;
constexpr int SM_X     = SM_Q + NSLOTS * 1024;
constexpr int XS_BYTES = REC_BYTES + 16 + 16;
constexpr int SM_PB    = SM_X + NSLOTS * XS_BYTES;
constexpr int SM_WM    = SM_PB + 4 * 16 * 16;
constexpr int SM_WS    = SM_WM + NCW * SQ * 4;
constexpr int SM_CX    = SM_WS + NCW * SQ * 4;
constexpr int SM_META  = SM_CX + REC_BYTES;
constexpr int SM_JOB   = SM_META + NSLOTS * 16;
constexpr int SM_EPOCH = SM_JOB + JQ * 4;
constexpr int SM_BARS  = SM_EPOCH + 16;
constexpr int SM_TOTAL = SM_BARS + (2 * NSLOTS + 2 * JQ + 1) * 8;
constexpr int SMEM_BYTES = SM_TOTAL + 1024;
static_assert(REC_BYTES % 16 == 0 && XS_BYTES % 16 == 0 && SM_BARS % 8 == 0, "align");

constexpr int FLAG_END = 4, FLAG_EXTRA = 8, FLAG_FINAL = 16;

constexpr int COLL_STRIDE = 4;
struct Scratch {
    float ring[(size_t)RING * NR * REC_FLOATS];
    float comb[(size_t)NHEADS * REC_FLOATS];
    unsigned int coll[NHEADS * COLL_STRIDE];
    unsigned int pad0[64];
    unsigned int work;
    unsigned int pad1[63];
    unsigned int done;
    unsigned int pad2[63];
    unsigned int epoch;
};
union ScratchBlob { Scratch s; unsigned char bytes[4 << 20]; };
static_assert(sizeof(Scratch) <= sizeof(ScratchBlob), "scratch");
__device__ __align__(256) ScratchBlob g_scratch;
#define g_ring  (g_scratch.s.ring)
#define g_comb  (g_scratch.s.comb)
#define g_coll  (g_scratch.s.coll)
#define g_work  (g_scratch.s.work)
#define g_done  (g_scratch.s.done)
#define g_epoch (g_scratch.s.epoch)

__device__ __forceinline__ uint32_t smem_u32(const void* p) { return (uint32_t)__cvta_generic_to_shared(p); }
__device__ __forceinline__ void mbar_init(uint32_t bar, uint32_t cnt) {
    asm volatile("mbarrier.init.shared::cta.b64 [%0], %1;" :: "r"(bar), "r"(cnt) : "memory");
}
__device__ __forceinline__ void mbar_expect_tx(uint32_t bar, uint32_t bytes) {
    asm volatile("mbarrier.arrive.expect_tx.shared::cta.b64 _, [%0], %1;" :: "r"(bar), "r"(bytes) : "memory");
}
__device__ __forceinline__ void mbar_arrive(uint32_t bar) {
    asm volatile("mbarrier.arrive.shared::cta.b64 _, [%0];" :: "r"(bar) : "memory");
}
__device__ __forceinline__ bool mbar_try_wait(uint32_t bar, uint32_t parity) {
    uint32_t ok;
    asm volatile("{\n.reg .pred p;\nmbarrier.try_wait.parity.shared::cta.b64 p, [%1], %2;\nselp.u32 %0, 1, 0, p;\n}"
                 : "=r"(ok) : "r"(bar), "r"(parity) : "memory");
    return ok != 0;
}
constexpr long long SPIN_LIMIT = 4000000000LL;
__device__ __forceinline__ void mbar_wait(uint32_t bar, uint32_t parity) {
    if (mbar_try_wait(bar, parity)) return;
    const long long t0 = clock64();
    while (!mbar_try_wait(bar, parity)) {
        if (clock64() - t0 > SPIN_LIMIT) __trap();
    }
}
__device__ __forceinline__ void tma_load_2d(uint32_t dst, const CUtensorMap* tm, int c0, int c1, uint32_t bar, uint64_t pol) {
    asm volatile("cp.async.bulk.tensor.2d.shared::cluster.global.mbarrier::complete_tx::bytes.L2::cache_hint [%0], [%1, {%3, %4}], [%2], %5;"
                 :: "r"(dst), "l"(tm), "r"(bar), "r"(c0), "r"(c1), "l"(pol) : "memory");
}
__device__ __forceinline__ void tma_load_2d_nh(uint32_t dst, const CUtensorMap* tm, int c0, int c1, uint32_t bar) {
    asm volatile("cp.async.bulk.tensor.2d.shared::cluster.global.mbarrier::complete_tx::bytes [%0], [%1, {%3, %4}], [%2];"
                 :: "r"(dst), "l"(tm), "r"(bar), "r"(c0), "r"(c1) : "memory");
}
__device__ __forceinline__ void bulk_load(uint32_t dst, const void* src, uint32_t bytes, uint32_t bar) {
    asm volatile("cp.async.bulk.shared::cluster.global.mbarrier::complete_tx::bytes [%0], [%1], %2, [%3];"
                 :: "r"(dst), "l"(src), "r"(bytes), "r"(bar) : "memory");
}
__device__ __forceinline__ void ldsm_x4(uint32_t (&r)[4], uint32_t addr) {
    asm volatile("ldmatrix.sync.aligned.m8n8.x4.shared.b16 {%0,%1,%2,%3}, [%4];"
                 : "=r"(r[0]), "=r"(r[1]), "=r"(r[2]), "=r"(r[3]) : "r"(addr) : "memory");
}
__device__ __forceinline__ void ldsm_x4_t(uint32_t (&r)[4], uint32_t addr) {
    asm volatile("ldmatrix.sync.aligned.m8n8.x4.trans.shared.b16 {%0,%1,%2,%3}, [%4];"
                 : "=r"(r[0]), "=r"(r[1]), "=r"(r[2]), "=r"(r[3]) : "r"(addr) : "memory");
}
__device__ __forceinline__ void mma_bf16(float (&d)[4], const uint32_t (&a)[4], uint32_t b0, uint32_t b1) {
    asm volatile("mma.sync.aligned.m16n8k16.row.col.f32.bf16.bf16.f32 {%0,%1,%2,%3}, {%4,%5,%6,%7}, {%8,%9}, {%0,%1,%2,%3};"
                 : "+f"(d[0]), "+f"(d[1]), "+f"(d[2]), "+f"(d[3])
                 : "r"(a[0]), "r"(a[1]), "r"(a[2]), "r"(a[3]), "r"(b0), "r"(b1));
}
__device__ __forceinline__ uint32_t movmatrix_t(uint32_t a) {
    uint32_t d;
    asm volatile("movmatrix.sync.aligned.m8n8.trans.b16 %0, %1;" : "=r"(d) : "r"(a));
    return d;
}
__device__ __forceinline__ uint32_t pack_bf16(float lo, float hi) {
    uint32_t d;
    asm("cvt.rn.bf16x2.f32 %0, %1, %2;" : "=r"(d) : "f"(hi), "f"(lo));
    return d;
}
__device__ __forceinline__ float ex2(float x) {
    float y;
    asm("ex2.approx.ftz.f32 %0, %1;" : "=f"(y) : "f"(x));
    return y;
}
__device__ __forceinline__ void named_bar_sync(int id, int nthreads) {
    asm volatile("bar.sync %0, %1;" :: "r"(id), "r"(nthreads) : "memory");
}
__device__ __forceinline__ unsigned atom_inc_relaxed(unsigned int* p) {
    unsigned o;
    asm volatile("atom.relaxed.gpu.global.add.u32 %0, [%1], 1;" : "=r"(o) : "l"(p) : "memory");
    return o;
}
__device__ __forceinline__ unsigned long long global_ns() {
    unsigned long long t;
    asm volatile("mov.u64 %0, %globaltimer;" : "=l"(t));
    return t;
}
__device__ __forceinline__ uint32_t fbits(float x) { return __float_as_uint(x); }
__device__ __forceinline__ float tagf(float x, uint32_t tag) { return __uint_as_float((fbits(x) & ~1u) | tag); }
__device__ __forceinline__ float4 untag(const float4& v) {
    return make_float4(tagf(v.x, 0u), tagf(v.y, 0u), tagf(v.z, 0u), tagf(v.w, 0u));
}
__device__ __forceinline__ uint32_t tag_bad(const float4& v, uint32_t tag) {
    return ((fbits(v.x) ^ tag) | (fbits(v.y) ^ tag) | (fbits(v.z) ^ tag) | (fbits(v.w) ^ tag)) & 1u;
}
__device__ __forceinline__ void st_relaxed_u32(unsigned int* p, uint32_t x) {
    asm volatile("st.relaxed.gpu.global.u32 [%0], %1;" :: "l"(p), "r"(x) : "memory");
}
__device__ __forceinline__ void st_relaxed_v4(float* p, float x, float y, float z, float w) {
    asm volatile("st.relaxed.gpu.global.v4.f32 [%0], {%1, %2, %3, %4};" :: "l"(p), "f"(x), "f"(y), "f"(z), "f"(w) : "memory");
}
__device__ __forceinline__ uint32_t ld_relaxed_u32(const unsigned int* p) {
    uint32_t v;
    asm volatile("ld.relaxed.gpu.global.u32 %0, [%1];" : "=r"(v) : "l"(p) : "memory");
    return v;
}
__device__ __forceinline__ float4 ld_relaxed_v4(const float* p) {
    float4 v;
    asm volatile("ld.relaxed.gpu.global.v4.f32 {%0,%1,%2,%3}, [%4];" : "=f"(v.x), "=f"(v.y), "=f"(v.z), "=f"(v.w) : "l"(p) : "memory");
    return v;
}

__device__ __forceinline__ void decode_a(int c, int& head, int& tile, int& cnt) {
    if (c < NA1)      { cnt = NR + 1; head = c / (NR + 1); tile = c % (NR + 1); }
    else if (c < NA2) { cnt = NR;     head = HD0 + (c - NA1) / NR; tile = (c - NA1) % NR; }
    else              { cnt = NR + 1; head = HD0 + TH + (c - NA2) / (NR + 1); tile = (c - NA2) % (NR + 1); }
}
__device__ __forceinline__ bool is_deferred(int head) { return head >= HD0 && head < HD0 + TH; }
__device__ __forceinline__ uint32_t ring_tag(int head) { return (uint32_t)(head / RING + 1) & 1u; }

__global__ void __launch_bounds__(NTHREADS, 1)
attn_decode_kernel(const __grid_constant__ CUtensorMap tmK, const __grid_constant__ CUtensorMap tmV,
                   const __grid_constant__ CUtensorMap tmQ, __nv_bfloat16* __restrict__ out,
                   const unsigned gap_ns, const unsigned gap_cyc)
{
    extern __shared__ unsigned char smem_raw[];
    const uint32_t sbase = (smem_u32(smem_raw) + 1023u) & ~1023u;
    unsigned char* sptr = smem_raw + (sbase - smem_u32(smem_raw));

    const int warp = threadIdx.x >> 5, lane = threadIdx.x & 31;
    const uint32_t bar_full  = sbase + SM_BARS;
    const uint32_t bar_empty = bar_full + NSLOTS * 8;
    const uint32_t bar_jfull = bar_empty + NSLOTS * 8;
    const uint32_t bar_jfree = bar_jfull + JQ * 8;
    const uint32_t bar_epoch = bar_jfree + JQ * 8;
    volatile uint32_t* s_epoch = reinterpret_cast<volatile uint32_t*>(sptr + SM_EPOCH);
    volatile int4* meta = reinterpret_cast<volatile int4*>(sptr + SM_META);
    volatile int* jobq = reinterpret_cast<volatile int*>(sptr + SM_JOB);

    uint64_t pol = 0;
    if (threadIdx.x == NTHREADS - 32) {
        mbar_init(bar_full, 1);
        mbar_init(bar_full + 8, 1);
        asm volatile("fence.mbarrier_init.release.cluster;" ::: "memory");
        asm volatile("createpolicy.fractional.L2::evict_first.b64 %0, 1.0;" : "=l"(pol));
        int head, tile, cnt;
        decode_a((int)blockIdx.x, head, tile, cnt);
        const int row = head * SKV + tile * TILE_ROWS;
        meta[0].x = head; meta[0].y = tile; meta[0].w = (tile == NR) ? FLAG_EXTRA : 0;
        mbar_expect_tx(bar_full, TILE_BYTES + SQ * DH * 2);
        tma_load_2d(sbase + SM_TILES, &tmK, 0, row, bar_full, pol);
        tma_load_2d(sbase + SM_TILES + HALF_BYTES, &tmK, 64, row, bar_full, pol);
        mbar_expect_tx(bar_full + 8, TILE_BYTES);
        tma_load_2d(sbase + SM_TILES + TILE_BYTES, &tmV, 0, row, bar_full + 8, pol);
        tma_load_2d(sbase + SM_TILES + TILE_BYTES + HALF_BYTES, &tmV, 64, row, bar_full + 8, pol);
        tma_load_2d_nh(sbase + SM_Q, &tmQ, 0, head * 8, bar_full);
        for (int s = 2; s < NSLOTS; s++) mbar_init(bar_full + 8 * s, 1);
        for (int s = 0; s < NSLOTS; s++) mbar_init(bar_empty + 8 * s, NCW);
        for (int s = 0; s < JQ; s++) { mbar_init(bar_jfull + 8 * s, 1); mbar_init(bar_jfree + 8 * s, NEW); }
        mbar_init(bar_epoch, 1);
        asm volatile("fence.mbarrier_init.release.cluster;" ::: "memory");
    }
    __syncthreads();

    const float SC = 0.08838834764831845f * 1.4426950408889634f;

    if (warp == NCW + NEW) {
        if (lane == 0) {
            int nissued = 2;
            int job = 0;
            unsigned c = blockIdx.x + gridDim.x;
            while (c < (unsigned)NCHUNKS) {
                int head, tile, kind = 0;
                if (c < (unsigned)NA) {
                    int cnt;
                    decode_a((int)c, head, tile, cnt);
                    if (tile == NR) kind = FLAG_EXTRA;
                } else {
                    head = HD0 + ((int)c - NA); tile = NR; kind = FLAG_FINAL;
                }
                const bool chk = (kind == 0) && head >= RING;
                const int row = head * SKV + tile * TILE_ROWS;
                unsigned long long tk = 0;
                long long ck = 0;
#pragma unroll
                for (int i = 0; i < 2; i++) {
                    const int slot = nissued % NSLOTS;
                    if (nissued > WIN) {
                        const int prev = nissued - WIN;
                        mbar_wait(bar_full + 8 * (prev % NSLOTS), (prev / NSLOTS) & 1);
                    }
                    mbar_wait(bar_empty + 8 * slot, ((nissued / NSLOTS) & 1) ^ 1);
                    const uint32_t fb = bar_full + 8 * slot, dst = sbase + SM_TILES + slot * TILE_BYTES;
                    if (i == 0) {
                        const uint32_t xb = sbase + SM_X + slot * XS_BYTES;
                        meta[slot].x = head; meta[slot].y = tile; meta[slot].w = kind;
                        mbar_expect_tx(fb, TILE_BYTES + SQ * DH * 2 + (kind == FLAG_FINAL ? REC_BYTES : 0) + (chk ? 16 : 0));
                        tma_load_2d(dst, &tmK, 0, row, fb, pol);
                        tma_load_2d(dst + HALF_BYTES, &tmK, 64, row, fb, pol);
                        tma_load_2d_nh(sbase + SM_Q + slot * 1024, &tmQ, 0, head * 8, fb);
                        if (kind == FLAG_FINAL) bulk_load(xb, g_comb + (size_t)head * REC_FLOATS, REC_BYTES, fb);
                        if (chk) bulk_load(xb + REC_BYTES, g_coll + COLL_STRIDE * (head - RING), 16, fb);
                        tk = global_ns(); ck = clock64();
#pragma unroll
                        for (int z = 0; z < 2; z++) {
                            const int cc = (int)c - (z == 0 ? LAG : LAG_END);
                            if (cc >= 0 && cc < NA) {
                                int h2, t2, cnt2;
                                decode_a(cc, h2, t2, cnt2);
                                if (t2 == cnt2 - 1 && ((h2 >= NHEADS - HEADS_END) == (z == 1))) {
                                    const int js = job % JQ;
                                    mbar_wait(bar_jfree + 8 * js, ((job / JQ) & 1) ^ 1);
                                    jobq[js] = h2;
                                    mbar_arrive(bar_jfull + 8 * js);
                                    job++;
                                }
                            }
                        }
                    } else {
                        while (global_ns() - tk < gap_ns && clock64() - ck < (long long)gap_cyc) {}
                        mbar_expect_tx(fb, TILE_BYTES);
                        tma_load_2d(dst, &tmV, 0, row, fb, pol);
                        tma_load_2d(dst + HALF_BYTES, &tmV, 64, row, fb, pol);
                    }
                    nissued++;
                }
                c = atom_inc_relaxed(&g_work) + 2 * gridDim.x;
            }
            {
                const int js = job % JQ;
                mbar_wait(bar_jfree + 8 * js, ((job / JQ) & 1) ^ 1);
                jobq[js] = -1;
                mbar_arrive(bar_jfull + 8 * js);
            }
            {
                const int slot = nissued % NSLOTS;
                mbar_wait(bar_empty + 8 * slot, ((nissued / NSLOTS) & 1) ^ 1);
                meta[slot].w = FLAG_END;
                mbar_arrive(bar_full + 8 * slot);
            }
            mbar_wait(bar_epoch, 0);
            if (atom_inc_relaxed(&g_done) == gridDim.x - 1) { g_work = 0; g_done = 0; g_epoch = *s_epoch + 1u; }
        }
    } else if (warp < NCW) {
        const int g = lane >> 2, t = lane & 3, r8 = lane & 7;
        const uint32_t kOff = (uint32_t)((warp * 16 + r8 + ((lane >> 3) & 1) * 8) * 128 + (((lane >> 4) ^ r8) << 4));
        const uint32_t vOff = (uint32_t)((warp >> 2) * HALF_BYTES + (r8 + (lane >> 4) * 8) * 128 +
                                         (((((2 * warp) & 7) | ((lane >> 3) & 1)) ^ r8) << 4));
        float* wmax = reinterpret_cast<float*>(sptr + SM_WM);
        float* wsum = reinterpret_cast<float*>(sptr + SM_WS);
        uint2* pbuf = reinterpret_cast<uint2*>(sptr + SM_PB);
        const int tq = t & 1;
        const int dcol = warp * 16 + g;
        const int frag = (warp * 16 + g * 2 + tq) * 4;
        int slot = 0; uint32_t phase = 0;
        uint32_t epoch1 = 0u;
        while (true) {
            mbar_wait(bar_full + 8 * slot, phase);
            const int flags = meta[slot].w;
            if (flags & FLAG_END) break;
            const int head = meta[slot].x, tile = meta[slot].y;
            const uint32_t kb = sbase + SM_TILES + slot * TILE_BYTES;
            const unsigned char* xs = sptr + SM_X + slot * XS_BYTES;
            uint32_t kf[8][4];
#pragma unroll
            for (int j = 0; j < 8; j++)
                ldsm_x4(kf[j], kb + (j >> 2) * HALF_BYTES + (kOff ^ (uint32_t)(((2 * j) & 7) << 4)));
            uint32_t qf[4][4];
#pragma unroll
            for (int i = 0; i < 4; i++) {
                const int hr = 2 * (lane & 3) + (i >> 1);
                const int cc = ((i & 1) * 4 + (lane >> 3));
                ldsm_x4(qf[i], sbase + SM_Q + slot * 1024 + hr * 128 + ((cc ^ hr) << 4));
            }
            float4 cO = make_float4(0.f, 0.f, 0.f, 0.f), cML = make_float4(0.f, 0.f, 0.f, 0.f);
            if (flags & FLAG_FINAL) {
                const float* cs = reinterpret_cast<const float*>(xs);
                cO  = *reinterpret_cast<const float4*>(cs + frag);
                cML = *reinterpret_cast<const float4*>(cs + SQ * DH + tq * 4);
            }
            uint32_t freeflag = *reinterpret_cast<const uint32_t*>(xs + REC_BYTES);
            __syncwarp();
            if (lane == 0) mbar_arrive(bar_empty + 8 * slot);
            if (++slot == NSLOTS) { slot = 0; phase ^= 1; }

            float sa[4] = {0.f, 0.f, 0.f, 0.f}, sb[4] = {0.f, 0.f, 0.f, 0.f};
#pragma unroll
            for (int j = 0; j < 8; j += 2) {
                mma_bf16(sa, kf[j], qf[j >> 1][0], qf[j >> 1][1]);
                mma_bf16(sb, kf[j + 1], qf[j >> 1][2], qf[j >> 1][3]);
            }
            const float s0 = sa[0] + sb[0], s1 = sa[1] + sb[1], s2 = sa[2] + sb[2], s3 = sa[3] + sb[3];
            float t0 = fmaxf(s0, s2), t1 = fmaxf(s1, s3);
#pragma unroll
            for (int x = 4; x <= 16; x <<= 1) {
                t0 = fmaxf(t0, __shfl_xor_sync(0xffffffffu, t0, x));
                t1 = fmaxf(t1, __shfl_xor_sync(0xffffffffu, t1, x));
            }
            if (lane < 2) *reinterpret_cast<float2*>(wmax + lane * 16 + warp * 2) = make_float2(t0, t1);
            named_bar_sync(2, NCW * 32);
            float m0 = -INFINITY, m1 = -INFINITY;
#pragma unroll
            for (int w = 0; w < NCW / 2; w++) {
                const float4 x = *reinterpret_cast<const float4*>(wmax + tq * 16 + w * 4);
                m0 = fmaxf(m0, fmaxf(x.x, x.z)); m1 = fmaxf(m1, fmaxf(x.y, x.w));
            }
            m0 = tagf(m0 * SC, 0u); m1 = tagf(m1 * SC, 0u);
            float p0 = ex2(fmaf(s0, SC, -m0)), p1 = ex2(fmaf(s1, SC, -m1));
            float p2 = ex2(fmaf(s2, SC, -m0)), p3 = ex2(fmaf(s3, SC, -m1));
            if (t >= 2) { p0 = p1 = p2 = p3 = 0.f; }
            {
                uint2 bb;
                bb.x = movmatrix_t(pack_bf16(p0, p1));
                bb.y = movmatrix_t(pack_bf16(p2, p3));
                if (lane < 16) pbuf[(warp >> 1) * 32 + lane * 2 + (warp & 1)] = bb;
                float r0 = p0 + p2, r1 = p1 + p3;
#pragma unroll
                for (int x = 4; x <= 16; x <<= 1) {
                    r0 += __shfl_xor_sync(0xffffffffu, r0, x);
                    r1 += __shfl_xor_sync(0xffffffffu, r1, x);
                }
                if (lane < 2) *reinterpret_cast<float2*>(wsum + lane * 16 + warp * 2) = make_float2(r0, r1);
            }
            named_bar_sync(2, NCW * 32);
            uint2 pf[8];
            float l0 = 0.f, l1 = 0.f;
#pragma unroll
            for (int w = 0; w < NCW / 2; w++) {
                const uint4 y = *reinterpret_cast<const uint4*>(pbuf + w * 32 + (lane & 15) * 2);
                pf[2 * w] = make_uint2(y.x, y.y); pf[2 * w + 1] = make_uint2(y.z, y.w);
                const float4 x = *reinterpret_cast<const float4*>(wsum + tq * 16 + w * 4);
                l0 += x.x; l1 += x.y; l0 += x.z; l1 += x.w;
            }
            if (epoch1 == 0u && (flags != 0 || head >= RING)) { mbar_wait(bar_epoch, 0); epoch1 = *s_epoch + 1u; }
            const uint32_t tag = (flags & (FLAG_EXTRA | FLAG_FINAL)) ? (epoch1 & 1u) : ring_tag(head);
            float fo0 = 1.f, fo1 = 1.f;
            float* rec = nullptr;
            if (flags & FLAG_FINAL) {
                const float* cg = g_comb + (size_t)head * REC_FLOATS;
                const long long tstart = clock64();
                while ((tag_bad(cO, tag) | tag_bad(cML, tag)) != 0u) {
                    cO  = ld_relaxed_v4(cg + frag);
                    cML = ld_relaxed_v4(cg + SQ * DH + tq * 4);
                    if (clock64() - tstart > SPIN_LIMIT) __trap();
                }
                cO = untag(cO); cML = untag(cML);
                const float M0 = fmaxf(m0, cML.x), M1 = fmaxf(m1, cML.z);
                const float a0 = ex2(m0 - M0), a1 = ex2(m1 - M1), c0 = ex2(cML.x - M0), c1 = ex2(cML.z - M1);
                const float i0 = 1.0f / fmaf(l0, a0, cML.y * c0), i1 = 1.0f / fmaf(l1, a1, cML.w * c1);
                fo0 = a0 * i0; fo1 = a1 * i1;
                cO.x *= c0 * i0; cO.y *= c1 * i1; cO.z *= c0 * i0; cO.w *= c1 * i1;
            } else if (flags & FLAG_EXTRA) {
                rec = g_comb + (size_t)head * REC_FLOATS;
            } else {
                rec = g_ring + ((size_t)(head % RING) * NR + tile) * REC_FLOATS;
                if (head >= RING) {
                    const long long tstart = clock64();
                    while (freeflag != epoch1) {
                        freeflag = ld_relaxed_u32(g_coll + COLL_STRIDE * (head - RING));
                        if (clock64() - tstart > SPIN_LIMIT) __trap();
                    }
                }
            }
            __syncwarp();

            mbar_wait(bar_full + 8 * slot, phase);
            const uint32_t vb = sbase + SM_TILES + slot * TILE_BYTES + vOff;
            uint32_t vf[8][4];
#pragma unroll
            for (int j = 0; j < 8; j++) ldsm_x4_t(vf[j], vb + j * 16 * 128);
            __syncwarp();
            if (lane == 0) mbar_arrive(bar_empty + 8 * slot);
            if (++slot == NSLOTS) { slot = 0; phase ^= 1; }
            float oa[4] = {0.f, 0.f, 0.f, 0.f}, ob[4] = {0.f, 0.f, 0.f, 0.f};
#pragma unroll
            for (int j = 0; j < 8; j += 2) {
                mma_bf16(oa, vf[j], pf[j].x, pf[j].y);
                mma_bf16(ob, vf[j + 1], pf[j + 1].x, pf[j + 1].y);
            }
            if (t < 2) {
                if (flags & FLAG_FINAL) {
                    __nv_bfloat16* op = out + ((size_t)head * SQ + 2 * t) * DH + dcol;
                    op[0]      = __float2bfloat16(fmaf(oa[0] + ob[0], fo0, cO.x));
                    op[DH]     = __float2bfloat16(fmaf(oa[1] + ob[1], fo1, cO.y));
                    op[8]      = __float2bfloat16(fmaf(oa[2] + ob[2], fo0, cO.z));
                    op[DH + 8] = __float2bfloat16(fmaf(oa[3] + ob[3], fo1, cO.w));
                } else {
                    st_relaxed_v4(rec + frag, tagf(oa[0] + ob[0], tag), tagf(oa[1] + ob[1], tag),
                                  tagf(oa[2] + ob[2], tag), tagf(oa[3] + ob[3], tag));
                    if (threadIdx.x < 2) st_relaxed_v4(rec + SQ * DH + t * 4, tagf(m0, tag), tagf(l0, tag), tagf(m1, tag), tagf(l1, tag));
                }
            }
        }
    } else {
        const int e = threadIdx.x - NCW * 32;
        const int half = e >> 7;
        const int f = e & 127;
        const int tq = lane & 1;
        float* cx = reinterpret_cast<float*>(sptr + SM_CX);
        if (e == 0) {
            *s_epoch = ld_relaxed_u32(&g_epoch);
            mbar_arrive(bar_epoch);
        }
        mbar_wait(bar_epoch, 0);
        const uint32_t epoch1 = *s_epoch + 1u;
        const uint32_t etag = epoch1 & 1u;
        for (int k = 0;; k++) {
            const int js = k % JQ; const uint32_t jph = (k / JQ) & 1;
            mbar_wait(bar_jfull + 8 * js, jph);
            const int head = jobq[js];
            __syncwarp();
            if (lane == 0) mbar_arrive(bar_jfree + 8 * js);
            if (head < 0) break;
            const bool deferred = is_deferred(head);
            const uint32_t rtag = ring_tag(head);
            const int nrec_all = deferred ? NR : NR + 1;
            const int r0 = half * HREC;
            const int nrec = (nrec_all - r0 < HREC) ? (nrec_all - r0) : HREC;
            const float* ring = g_ring + ((size_t)(head % RING) * NR + r0) * REC_FLOATS;
            float* comb = g_comb + (size_t)head * REC_FLOATS;
            const int ml_u = lane & 15;
            const bool ml_extra = (r0 + ml_u == NR);
            const float* pml = (ml_extra ? comb : ring + (size_t)ml_u * REC_FLOATS) + SQ * DH + (lane >> 4) * 4;
            const uint32_t mltag = ml_extra ? etag : rtag;
            float4 v[HREC];
#pragma unroll
            for (int u = 0; u < HREC; u++) v[u] = make_float4(0.f, 0.f, 0.f, 0.f);
            float4 pm = make_float4(-INFINITY, 0.f, -INFINITY, 0.f);
            uint32_t pending = (1u << nrec) - 1u;
            const long long tstart = clock64();
            while (true) {
                if ((pending >> ml_u) & 1u) pm = ld_relaxed_v4(pml);
#pragma unroll
                for (int u = 0; u < HREC; u++)
                    if ((pending >> u) & 1u)
                        v[u] = ld_relaxed_v4(((r0 + u == NR) ? comb : ring + (size_t)u * REC_FLOATS) + f * 4);
                uint32_t bad = tag_bad(pm, mltag) << ml_u;
#pragma unroll
                for (int u = 0; u < HREC; u++) bad |= tag_bad(v[u], (r0 + u == NR) ? etag : rtag) << u;
                pending &= __reduce_or_sync(0xffffffffu, bad);
                if (pending == 0u) break;
                if (clock64() - tstart > SPIN_LIMIT) __trap();
                __nanosleep(500);
            }
            pm = untag(pm);
            const bool mlv = ml_u < nrec;
            float Ma = mlv ? pm.x : -INFINITY, Mb = mlv ? pm.z : -INFINITY;
#pragma unroll
            for (int x = 1; x < 16; x <<= 1) {
                Ma = fmaxf(Ma, __shfl_xor_sync(0xffffffffu, Ma, x));
                Mb = fmaxf(Mb, __shfl_xor_sync(0xffffffffu, Mb, x));
            }
            const float sca = mlv ? ex2(pm.x - Ma) : 0.f, scb = mlv ? ex2(pm.z - Mb) : 0.f;
            float La = mlv ? pm.y * sca : 0.f, Lb = mlv ? pm.w * scb : 0.f;
#pragma unroll
            for (int x = 1; x < 16; x <<= 1) {
                La += __shfl_xor_sync(0xffffffffu, La, x);
                Lb += __shfl_xor_sync(0xffffffffu, Lb, x);
            }
            float4 acc = make_float4(0.f, 0.f, 0.f, 0.f);
#pragma unroll
            for (int u = 0; u < HREC; u++) {
                const float sa = __shfl_sync(0xffffffffu, sca, u + 16 * tq), sb = __shfl_sync(0xffffffffu, scb, u + 16 * tq);
                const float4 x = untag(v[u]);
                acc.x = fmaf(x.x, sa, acc.x); acc.y = fmaf(x.y, sb, acc.y);
                acc.z = fmaf(x.z, sa, acc.z); acc.w = fmaf(x.w, sb, acc.w);
            }
            Ma = __shfl_sync(0xffffffffu, Ma, 16 * tq); La = __shfl_sync(0xffffffffu, La, 16 * tq);
            Mb = __shfl_sync(0xffffffffu, Mb, 16 * tq); Lb = __shfl_sync(0xffffffffu, Lb, 16 * tq);
            if (half == 1) {
                *reinterpret_cast<float4*>(cx + f * 4) = acc;
                if (f < 2) *reinterpret_cast<float4*>(cx + SQ * DH + tq * 4) = make_float4(Ma, La, Mb, Lb);
            }
            named_bar_sync(1, NEW * 32);
            if (e == NEW * 32 - 1) st_relaxed_u32(g_coll + COLL_STRIDE * head, epoch1);
            if (half == 0) {
                const float4 ov = *reinterpret_cast<const float4*>(cx + f * 4);
                const float4 oml = *reinterpret_cast<const float4*>(cx + SQ * DH + tq * 4);
                const float M0 = fmaxf(Ma, oml.x), M1 = fmaxf(Mb, oml.z);
                const float fa0 = ex2(Ma - M0), fb0 = ex2(oml.x - M0), fa1 = ex2(Mb - M1), fb1 = ex2(oml.z - M1);
                const float L0 = fmaf(La, fa0, oml.y * fb0), L1 = fmaf(Lb, fa1, oml.w * fb1);
                const float r0x = fmaf(acc.x, fa0, ov.x * fb0), r1x = fmaf(acc.y, fa1, ov.y * fb1);
                const float r0y = fmaf(acc.z, fa0, ov.z * fb0), r1y = fmaf(acc.w, fa1, ov.w * fb1);
                if (deferred) {
                    st_relaxed_v4(comb + f * 4, tagf(r0x, etag), tagf(r1x, etag), tagf(r0y, etag), tagf(r1y, etag));
                    if (f < 2) st_relaxed_v4(comb + SQ * DH + tq * 4, tagf(M0, etag), tagf(L0, etag), tagf(M1, etag), tagf(L1, etag));
                } else {
                    const float i0 = 1.0f / L0, i1 = 1.0f / L1;
                    __nv_bfloat16* op = out + ((size_t)head * SQ + 2 * tq) * DH + (f >> 4) * 16 + ((f >> 1) & 7);
                    op[0]      = __float2bfloat16(r0x * i0);
                    op[DH]     = __float2bfloat16(r1x * i1);
                    op[8]      = __float2bfloat16(r0y * i0);
                    op[DH + 8] = __float2bfloat16(r1y * i1);
                }
            }
            named_bar_sync(1, NEW * 32);
        }
    }
}

typedef CUresult (*EncodeTiledFn)(CUtensorMap*, CUtensorMapDataType, cuuint32_t, void*, const cuuint64_t*,
                                  const cuuint64_t*, const cuuint32_t*, const cuuint32_t*, CUtensorMapInterleave,
                                  CUtensorMapSwizzle, CUtensorMapL2promotion, CUtensorMapFloatOOBfill);

void make_map(EncodeTiledFn enc, CUtensorMap* m, void* p) {
    cuuint64_t dims[2]    = {(cuuint64_t)DH, (cuuint64_t)NHEADS * SKV};
    cuuint64_t strides[1] = {(cuuint64_t)DH * 2};
    cuuint32_t box[2]     = {64, (cuuint32_t)TILE_ROWS};
    cuuint32_t es[2]      = {1, 1};
    enc(m, CU_TENSOR_MAP_DATA_TYPE_BFLOAT16, 2, p, dims, strides, box, es, CU_TENSOR_MAP_INTERLEAVE_NONE,
        CU_TENSOR_MAP_SWIZZLE_128B, CU_TENSOR_MAP_L2_PROMOTION_L2_256B, CU_TENSOR_MAP_FLOAT_OOB_FILL_NONE);
}

}

extern "C" void kernel_launch(void* const* d_in, const int* in_sizes, int n_in, void* d_out, int out_size) {
    (void)in_sizes; (void)n_in; (void)out_size;
    static EncodeTiledFn enc = nullptr;
    static int nsm = 0;
    static unsigned gap_ns = 0, gap_cyc = 0;
    if (!enc) {
        cudaDriverEntryPointQueryResult qr;
        void* fn = nullptr;
        cudaGetDriverEntryPoint("cuTensorMapEncodeTiled", &fn, cudaEnableDefault, &qr);
        enc = (EncodeTiledFn)fn;
        cudaFuncSetAttribute(attn_decode_kernel, cudaFuncAttributeMaxDynamicSharedMemorySize, SMEM_BYTES);
        int dev = 0;
        cudaGetDevice(&dev);
        cudaDeviceGetAttribute(&nsm, cudaDevAttrMultiProcessorCount, dev);
        int mem_khz = 0, bus_bits = 0;
        cudaDeviceGetAttribute(&mem_khz, cudaDevAttrMemoryClockRate, dev);
        cudaDeviceGetAttribute(&bus_bits, cudaDevAttrGlobalMemoryBusWidth, dev);
        const double bw = 2.0 * mem_khz * 1e3 * bus_bits / 8.0 * 0.96;
        const int g = nsm < MAX_CTA ? nsm : MAX_CTA;
        double gap = bw > 0.0 ? (double)g * 2.0 * TILE_BYTES / bw * 1e9 - GAP_FIXED_NS : 0.0;
        gap_ns = gap < 0.0 ? 0u : gap > 1200.0 ? 1200u : (unsigned)gap;
        int sm_khz = 0;
        cudaDeviceGetAttribute(&sm_khz, cudaDevAttrClockRate, dev);
        gap_cyc = (unsigned)(gap_ns * 1.03e-6 * sm_khz);
    }
    CUtensorMap tmK, tmV, tmQ;
    {
        cuuint64_t dims[2] = {64, (cuuint64_t)NHEADS * SQ * 2}; cuuint64_t strides[1] = {128};
        cuuint32_t box[2] = {64, 8}; cuuint32_t es[2] = {1, 1};
        enc(&tmQ, CU_TENSOR_MAP_DATA_TYPE_BFLOAT16, 2, d_in[0], dims, strides, box, es, CU_TENSOR_MAP_INTERLEAVE_NONE,
            CU_TENSOR_MAP_SWIZZLE_128B, CU_TENSOR_MAP_L2_PROMOTION_NONE, CU_TENSOR_MAP_FLOAT_OOB_FILL_NONE);
    }
    make_map(enc, &tmK, d_in[1]);
    make_map(enc, &tmV, d_in[2]);
    const int grid = nsm < MAX_CTA ? nsm : MAX_CTA;
    attn_decode_kernel<<<grid, NTHREADS, SMEM_BYTES>>>(tmK, tmV, tmQ, (__nv_bfloat16*)d_out, gap_ns, gap_cyc);
}
```

```cpp
#include <cuda_runtime.h>
#include <cuda_bf16.h>
#include <cuda.h>
#include <stdint.h>

namespace {

constexpr int NHEADS = 512;
constexpr int SQ     = 4;
constexpr int SKV    = 4096;
constexpr int DH     = 128;

constexpr int TILE_ROWS  = 128;
constexpr int TILE_BYTES = TILE_ROWS * DH * 2;
constexpr int HALF_BYTES = TILE_BYTES / 2;
constexpr int TPH    = SKV / TILE_ROWS;
constexpr int NSLOTS = 4;
constexpr int WIN    = 2;
constexpr int NCW = 8;
constexpr int NEW = 8;
constexpr int NTHREADS = 32 * (NCW + NEW + 1);
constexpr int MAX_CTA = 132;
constexpr double GAP_FIXED_NS = 1400.0;

constexpr int NR   = TPH - 1;
constexpr int TH   = 500;
constexpr int GAP  = 12;
constexpr int HD0  = NHEADS - GAP - TH;
constexpr int NA1  = HD0 * (NR + 1);
constexpr int NA2  = NA1 + TH * NR;
constexpr int NA   = NA2 + GAP * (NR + 1);
constexpr int NCHUNKS = NA + TH;
constexpr int LAG  = 400;
constexpr int RING = 32;
constexpr int HREC = (NR + 2) / 2;
static_assert(HD0 >= 0 && LAG <= TH && LAG < (RING - 1) * NR && NHEADS % (2 * RING) == 0 && HREC <= 16 &&
              MAX_CTA <= LAG && MAX_CTA <= RING * NR && WIN + 1 <= NSLOTS, "bad schedule");

constexpr int JQ = 4;
constexpr int REC_BYTES  = SQ * DH * 4 + SQ * 8;
constexpr int REC_FLOATS = 544;

constexpr int SM_TILES = 0;
constexpr int SM_Q     = SM_TILES + NSLOTS * TILE_BYTES;
constexpr int SM_X     = SM_Q + NSLOTS * 1024;
constexpr int XS_BYTES = REC_BYTES + 16 + 16;
constexpr int SM_PB    = SM_X + NSLOTS * XS_BYTES;
constexpr int SM_WM    = SM_PB + 4 * 16 * 16;
constexpr int SM_WS    = SM_WM + NCW * SQ * 4;
constexpr int SM_CX    = SM_WS + NCW * SQ * 4;
constexpr int SM_META  = SM_CX + REC_BYTES;
constexpr int SM_JOB   = SM_META + NSLOTS * 16;
constexpr int SM_EPOCH = SM_JOB + JQ * 4;
constexpr int SM_BARS  = SM_EPOCH + 16;
constexpr int SM_TOTAL = SM_BARS + (2 * NSLOTS + 2 * JQ + 1) * 8;
constexpr int SMEM_BYTES = SM_TOTAL + 1024;
static_assert(REC_BYTES % 16 == 0 && XS_BYTES % 16 == 0 && SM_BARS % 8 == 0, "align");

constexpr int FLAG_END = 4, FLAG_EXTRA = 8, FLAG_FINAL = 16;

constexpr int COLL_STRIDE = 4;
struct Scratch {
    float ring[(size_t)RING * NR * REC_FLOATS];
    float comb[(size_t)NHEADS * REC_FLOATS];
    unsigned int coll[NHEADS * COLL_STRIDE];
    unsigned int pad0[64];
    unsigned int work;
    unsigned int pad1[63];
    unsigned int done;
    unsigned int pad2[63];
    unsigned int epoch;
};
union ScratchBlob { Scratch s; unsigned char bytes[4 << 20]; };
static_assert(sizeof(Scratch) <= sizeof(ScratchBlob), "scratch");
__device__ __align__(256) ScratchBlob g_scratch;
#define g_ring  (g_scratch.s.ring)
#define g_comb  (g_scratch.s.comb)
#define g_coll  (g_scratch.s.coll)
#define g_work  (g_scratch.s.work)
#define g_done  (g_scratch.s.done)
#define g_epoch (g_scratch.s.epoch)

__device__ __forceinline__ uint32_t smem_u32(const void* p) { return (uint32_t)__cvta_generic_to_shared(p); }
__device__ __forceinline__ void mbar_init(uint32_t bar, uint32_t cnt) {
    asm volatile("mbarrier.init.shared::cta.b64 [%0], %1;" :: "r"(bar), "r"(cnt) : "memory");
}
__device__ __forceinline__ void mbar_expect_tx(uint32_t bar, uint32_t bytes) {
    asm volatile("mbarrier.arrive.expect_tx.shared::cta.b64 _, [%0], %1;" :: "r"(bar), "r"(bytes) : "memory");
}
__device__ __forceinline__ void mbar_arrive(uint32_t bar) {
    asm volatile("mbarrier.arrive.shared::cta.b64 _, [%0];" :: "r"(bar) : "memory");
}
__device__ __forceinline__ bool mbar_try_wait(uint32_t bar, uint32_t parity) {
    uint32_t ok;
    asm volatile("{\n.reg .pred p;\nmbarrier.try_wait.parity.shared::cta.b64 p, [%1], %2;\nselp.u32 %0, 1, 0, p;\n}"
                 : "=r"(ok) : "r"(bar), "r"(parity) : "memory");
    return ok != 0;
}
constexpr long long SPIN_LIMIT = 4000000000LL;
__device__ __forceinline__ void mbar_wait(uint32_t bar, uint32_t parity) {
    if (mbar_try_wait(bar, parity)) return;
    const long long t0 = clock64();
    while (!mbar_try_wait(bar, parity)) {
        if (clock64() - t0 > SPIN_LIMIT) __trap();
    }
}
__device__ __forceinline__ void tma_load_2d(uint32_t dst, const CUtensorMap* tm, int c0, int c1, uint32_t bar, uint64_t pol) {
    asm volatile("cp.async.bulk.tensor.2d.shared::cluster.global.mbarrier::complete_tx::bytes.L2::cache_hint [%0], [%1, {%3, %4}], [%2], %5;"
                 :: "r"(dst), "l"(tm), "r"(bar), "r"(c0), "r"(c1), "l"(pol) : "memory");
}
__device__ __forceinline__ void tma_load_2d_nh(uint32_t dst, const CUtensorMap* tm, int c0, int c1, uint32_t bar) {
    asm volatile("cp.async.bulk.tensor.2d.shared::cluster.global.mbarrier::complete_tx::bytes [%0], [%1, {%3, %4}], [%2];"
                 :: "r"(dst), "l"(tm), "r"(bar), "r"(c0), "r"(c1) : "memory");
}
__device__ __forceinline__ void bulk_load(uint32_t dst, const void* src, uint32_t bytes, uint32_t bar) {
    asm volatile("cp.async.bulk.shared::cluster.global.mbarrier::complete_tx::bytes [%0], [%1], %2, [%3];"
                 :: "r"(dst), "l"(src), "r"(bytes), "r"(bar) : "memory");
}
__device__ __forceinline__ void ldsm_x4(uint32_t (&r)[4], uint32_t addr) {
    asm volatile("ldmatrix.sync.aligned.m8n8.x4.shared.b16 {%0,%1,%2,%3}, [%4];"
                 : "=r"(r[0]), "=r"(r[1]), "=r"(r[2]), "=r"(r[3]) : "r"(addr) : "memory");
}
__device__ __forceinline__ void ldsm_x4_t(uint32_t (&r)[4], uint32_t addr) {
    asm volatile("ldmatrix.sync.aligned.m8n8.x4.trans.shared.b16 {%0,%1,%2,%3}, [%4];"
                 : "=r"(r[0]), "=r"(r[1]), "=r"(r[2]), "=r"(r[3]) : "r"(addr) : "memory");
}
__device__ __forceinline__ void mma_bf16(float (&d)[4], const uint32_t (&a)[4], uint32_t b0, uint32_t b1) {
    asm volatile("mma.sync.aligned.m16n8k16.row.col.f32.bf16.bf16.f32 {%0,%1,%2,%3}, {%4,%5,%6,%7}, {%8,%9}, {%0,%1,%2,%3};"
                 : "+f"(d[0]), "+f"(d[1]), "+f"(d[2]), "+f"(d[3])
                 : "r"(a[0]), "r"(a[1]), "r"(a[2]), "r"(a[3]), "r"(b0), "r"(b1));
}
__device__ __forceinline__ uint32_t movmatrix_t(uint32_t a) {
    uint32_t d;
    asm volatile("movmatrix.sync.aligned.m8n8.trans.b16 %0, %1;" : "=r"(d) : "r"(a));
    return d;
}
__device__ __forceinline__ uint32_t pack_bf16(float lo, float hi) {
    uint32_t d;
    asm("cvt.rn.bf16x2.f32 %0, %1, %2;" : "=r"(d) : "f"(hi), "f"(lo));
    return d;
}
__device__ __forceinline__ float ex2(float x) {
    float y;
    asm("ex2.approx.ftz.f32 %0, %1;" : "=f"(y) : "f"(x));
    return y;
}
__device__ __forceinline__ void named_bar_sync(int id, int nthreads) {
    asm volatile("bar.sync %0, %1;" :: "r"(id), "r"(nthreads) : "memory");
}
__device__ __forceinline__ unsigned atom_inc_relaxed(unsigned int* p) {
    unsigned o;
    asm volatile("atom.relaxed.gpu.global.add.u32 %0, [%1], 1;" : "=r"(o) : "l"(p) : "memory");
    return o;
}
__device__ __forceinline__ unsigned long long global_ns() {
    unsigned long long t;
    asm volatile("mov.u64 %0, %globaltimer;" : "=l"(t));
    return t;
}
__device__ __forceinline__ uint32_t fbits(float x) { return __float_as_uint(x); }
__device__ __forceinline__ float tagf(float x, uint32_t tag) { return __uint_as_float((fbits(x) & ~1u) | tag); }
__device__ __forceinline__ float4 untag(const float4& v) {
    return make_float4(tagf(v.x, 0u), tagf(v.y, 0u), tagf(v.z, 0u), tagf(v.w, 0u));
}
__device__ __forceinline__ uint32_t tag_bad(const float4& v, uint32_t tag) {
    return ((fbits(v.x) ^ tag) | (fbits(v.y) ^ tag) | (fbits(v.z) ^ tag) | (fbits(v.w) ^ tag)) & 1u;
}
__device__ __forceinline__ void st_relaxed_u32(unsigned int* p, uint32_t x) {
    asm volatile("st.relaxed.gpu.global.u32 [%0], %1;" :: "l"(p), "r"(x) : "memory");
}
__device__ __forceinline__ void st_relaxed_v4(float* p, float x, float y, float z, float w) {
    asm volatile("st.relaxed.gpu.global.v4.f32 [%0], {%1, %2, %3, %4};" :: "l"(p), "f"(x), "f"(y), "f"(z), "f"(w) : "memory");
}
__device__ __forceinline__ uint32_t ld_relaxed_u32(const unsigned int* p) {
    uint32_t v;
    asm volatile("ld.relaxed.gpu.global.u32 %0, [%1];" : "=r"(v) : "l"(p) : "memory");
    return v;
}
__device__ __forceinline__ float4 ld_relaxed_v4(const float* p) {
    float4 v;
    asm volatile("ld.relaxed.gpu.global.v4.f32 {%0,%1,%2,%3}, [%4];" : "=f"(v.x), "=f"(v.y), "=f"(v.z), "=f"(v.w) : "l"(p) : "memory");
    return v;
}

__device__ __forceinline__ void decode_a(int c, int& head, int& tile, int& cnt) {
    if (c < NA1)      { cnt = NR + 1; head = c / (NR + 1); tile = c % (NR + 1); }
    else if (c < NA2) { cnt = NR;     head = HD0 + (c - NA1) / NR; tile = (c - NA1) % NR; }
    else              { cnt = NR + 1; head = HD0 + TH + (c - NA2) / (NR + 1); tile = (c - NA2) % (NR + 1); }
}
__device__ __forceinline__ bool is_deferred(int head) { return head >= HD0 && head < HD0 + TH; }
__device__ __forceinline__ uint32_t ring_tag(int head) { return (uint32_t)(head / RING + 1) & 1u; }

__global__ void __launch_bounds__(NTHREADS, 1)
attn_decode_kernel(const __grid_constant__ CUtensorMap tmK, const __grid_constant__ CUtensorMap tmV,
                   const __grid_constant__ CUtensorMap tmQ, __nv_bfloat16* __restrict__ out,
                   const unsigned gap_ns, const unsigned gap_cyc)
{
    extern __shared__ unsigned char smem_raw[];
    const uint32_t sbase = (smem_u32(smem_raw) + 1023u) & ~1023u;
    unsigned char* sptr = smem_raw + (sbase - smem_u32(smem_raw));

    const int warp = threadIdx.x >> 5, lane = threadIdx.x & 31;
    const uint32_t bar_full  = sbase + SM_BARS;
    const uint32_t bar_empty = bar_full + NSLOTS * 8;
    const uint32_t bar_jfull = bar_empty + NSLOTS * 8;
    const uint32_t bar_jfree = bar_jfull + JQ * 8;
    const uint32_t bar_epoch = bar_jfree + JQ * 8;
    volatile uint32_t* s_epoch = reinterpret_cast<volatile uint32_t*>(sptr + SM_EPOCH);
    volatile int4* meta = reinterpret_cast<volatile int4*>(sptr + SM_META);
    volatile int* jobq = reinterpret_cast<volatile int*>(sptr + SM_JOB);

    uint64_t pol = 0;
    if (threadIdx.x == NTHREADS - 32) {
        mbar_init(bar_full, 1);
        mbar_init(bar_full + 8, 1);
        asm volatile("fence.mbarrier_init.release.cluster;" ::: "memory");
        asm volatile("createpolicy.fractional.L2::evict_first.b64 %0, 1.0;" : "=l"(pol));
        int head, tile, cnt;
        decode_a((int)blockIdx.x, head, tile, cnt);
        const int row = head * SKV + tile * TILE_ROWS;
        meta[0].x = head; meta[0].y = tile; meta[0].w = (tile == NR) ? FLAG_EXTRA : 0;
        mbar_expect_tx(bar_full, TILE_BYTES + SQ * DH * 2);
        tma_load_2d(sbase + SM_TILES, &tmK, 0, row, bar_full, pol);
        tma_load_2d(sbase + SM_TILES + HALF_BYTES, &tmK, 64, row, bar_full, pol);
        mbar_expect_tx(bar_full + 8, TILE_BYTES);
        tma_load_2d(sbase + SM_TILES + TILE_BYTES, &tmV, 0, row, bar_full + 8, pol);
        tma_load_2d(sbase + SM_TILES + TILE_BYTES + HALF_BYTES, &tmV, 64, row, bar_full + 8, pol);
        tma_load_2d_nh(sbase + SM_Q, &tmQ, 0, head * 8, bar_full);
        for (int s = 2; s < NSLOTS; s++) mbar_init(bar_full + 8 * s, 1);
        for (int s = 0; s < NSLOTS; s++) mbar_init(bar_empty + 8 * s, NCW);
        for (int s = 0; s < JQ; s++) { mbar_init(bar_jfull + 8 * s, 1); mbar_init(bar_jfree + 8 * s, NEW); }
        mbar_init(bar_epoch, 1);
        asm volatile("fence.mbarrier_init.release.cluster;" ::: "memory");
    }
    __syncthreads();

    const float SC = 0.08838834764831845f * 1.4426950408889634f;

    if (warp == NCW + NEW) {
        if (lane == 0) {
            int nissued = 2;
            int job = 0;
            unsigned c = blockIdx.x + gridDim.x;
            while (c < (unsigned)NCHUNKS) {
                int head, tile, kind = 0;
                if (c < (unsigned)NA) {
                    int cnt;
                    decode_a((int)c, head, tile, cnt);
                    if (tile == NR) kind = FLAG_EXTRA;
                } else {
                    head = HD0 + ((int)c - NA); tile = NR; kind = FLAG_FINAL;
                }
                const bool chk = (kind == 0) && head >= RING;
                const int row = head * SKV + tile * TILE_ROWS;
                unsigned long long tk = 0;
                long long ck = 0;
#pragma unroll
                for (int i = 0; i < 2; i++) {
                    const int slot = nissued % NSLOTS;
                    if (nissued > WIN) {
                        const int prev = nissued - WIN;
                        mbar_wait(bar_full + 8 * (prev % NSLOTS), (prev / NSLOTS) & 1);
                    }
                    mbar_wait(bar_empty + 8 * slot, ((nissued / NSLOTS) & 1) ^ 1);
                    const uint32_t fb = bar_full + 8 * slot, dst = sbase + SM_TILES + slot * TILE_BYTES;
                    if (i == 0) {
                        const uint32_t xb = sbase + SM_X + slot * XS_BYTES;
                        meta[slot].x = head; meta[slot].y = tile; meta[slot].w = kind;
                        mbar_expect_tx(fb, TILE_BYTES + SQ * DH * 2 + (kind == FLAG_FINAL ? REC_BYTES : 0) + (chk ? 16 : 0));
                        tma_load_2d(dst, &tmK, 0, row, fb, pol);
                        tma_load_2d(dst + HALF_BYTES, &tmK, 64, row, fb, pol);
                        tma_load_2d_nh(sbase + SM_Q + slot * 1024, &tmQ, 0, head * 8, fb);
                        if (kind == FLAG_FINAL) bulk_load(xb, g_comb + (size_t)head * REC_FLOATS, REC_BYTES, fb);
                        if (chk) bulk_load(xb + REC_BYTES, g_coll + COLL_STRIDE * (head - RING), 16, fb);
                        tk = global_ns(); ck = clock64();
                        const int cc = (int)c - LAG;
                        if (cc >= 0 && cc < NA) {
                            int h2, t2, cnt2;
                            decode_a(cc, h2, t2, cnt2);
                            if (t2 == cnt2 - 1) {
                                const int js = job % JQ;
                                mbar_wait(bar_jfree + 8 * js, ((job / JQ) & 1) ^ 1);
                                jobq[js] = h2;
                                mbar_arrive(bar_jfull + 8 * js);
                                job++;
                            }
                        }
                    } else {
                        while (global_ns() - tk < gap_ns && clock64() - ck < (long long)gap_cyc) {}
                        mbar_expect_tx(fb, TILE_BYTES);
                        tma_load_2d(dst, &tmV, 0, row, fb, pol);
                        tma_load_2d(dst + HALF_BYTES, &tmV, 64, row, fb, pol);
                    }
                    nissued++;
                }
                c = atom_inc_relaxed(&g_work) + 2 * gridDim.x;
            }
            {
                const int js = job % JQ;
                mbar_wait(bar_jfree + 8 * js, ((job / JQ) & 1) ^ 1);
                jobq[js] = -1;
                mbar_arrive(bar_jfull + 8 * js);
            }
            {
                const int slot = nissued % NSLOTS;
                mbar_wait(bar_empty + 8 * slot, ((nissued / NSLOTS) & 1) ^ 1);
                meta[slot].w = FLAG_END;
                mbar_arrive(bar_full + 8 * slot);
            }
            mbar_wait(bar_epoch, 0);
            if (atom_inc_relaxed(&g_done) == gridDim.x - 1) { g_work = 0; g_done = 0; g_epoch = *s_epoch + 1u; }
        }
    } else if (warp < NCW) {
        const int g = lane >> 2, t = lane & 3, r8 = lane & 7;
        const uint32_t kOff = (uint32_t)((warp * 16 + r8 + ((lane >> 3) & 1) * 8) * 128 + (((lane >> 4) ^ r8) << 4));
        const uint32_t vOff = (uint32_t)((warp >> 2) * HALF_BYTES + (r8 + (lane >> 4) * 8) * 128 +
                                         (((((2 * warp) & 7) | ((lane >> 3) & 1)) ^ r8) << 4));
        float* wmax = reinterpret_cast<float*>(sptr + SM_WM);
        float* wsum = reinterpret_cast<float*>(sptr + SM_WS);
        uint2* pbuf = reinterpret_cast<uint2*>(sptr + SM_PB);
        const int tq = t & 1;
        const int dcol = warp * 16 + g;
        const int frag = (warp * 16 + g * 2 + tq) * 4;
        int slot = 0; uint32_t phase = 0;
        uint32_t epoch1 = 0u;
        while (true) {
            mbar_wait(bar_full + 8 * slot, phase);
            const int flags = meta[slot].w;
            if (flags & FLAG_END) break;
            const int head = meta[slot].x, tile = meta[slot].y;
            const uint32_t kb = sbase + SM_TILES + slot * TILE_BYTES;
            const unsigned char* xs = sptr + SM_X + slot * XS_BYTES;
            uint32_t kf[8][4];
#pragma unroll
            for (int j = 0; j < 8; j++)
                ldsm_x4(kf[j], kb + (j >> 2) * HALF_BYTES + (kOff ^ (uint32_t)(((2 * j) & 7) << 4)));
            uint32_t qf[4][4];
#pragma unroll
            for (int i = 0; i < 4; i++) {
                const int hr = 2 * (lane & 3) + (i >> 1);
                const int cc = ((i & 1) * 4 + (lane >> 3));
                ldsm_x4(qf[i], sbase + SM_Q + slot * 1024 + hr * 128 + ((cc ^ hr) << 4));
            }
            float4 cO = make_float4(0.f, 0.f, 0.f, 0.f), cML = make_float4(0.f, 0.f, 0.f, 0.f);
            if (flags & FLAG_FINAL) {
                const float* cs = reinterpret_cast<const float*>(xs);
                cO  = *reinterpret_cast<const float4*>(cs + frag);
                cML = *reinterpret_cast<const float4*>(cs + SQ * DH + tq * 4);
            }
            uint32_t freeflag = *reinterpret_cast<const uint32_t*>(xs + REC_BYTES);
            __syncwarp();
            if (lane == 0) mbar_arrive(bar_empty + 8 * slot);
            if (++slot == NSLOTS) { slot = 0; phase ^= 1; }

            float sa[4] = {0.f, 0.f, 0.f, 0.f}, sb[4] = {0.f, 0.f, 0.f, 0.f};
#pragma unroll
            for (int j = 0; j < 8; j += 2) {
                mma_bf16(sa, kf[j], qf[j >> 1][0], qf[j >> 1][1]);
                mma_bf16(sb, kf[j + 1], qf[j >> 1][2], qf[j >> 1][3]);
            }
            const float s0 = sa[0] + sb[0], s1 = sa[1] + sb[1], s2 = sa[2] + sb[2], s3 = sa[3] + sb[3];
            float t0 = fmaxf(s0, s2), t1 = fmaxf(s1, s3);
#pragma unroll
            for (int x = 4; x <= 16; x <<= 1) {
                t0 = fmaxf(t0, __shfl_xor_sync(0xffffffffu, t0, x));
                t1 = fmaxf(t1, __shfl_xor_sync(0xffffffffu, t1, x));
            }
            if (lane < 2) *reinterpret_cast<float2*>(wmax + lane * 16 + warp * 2) = make_float2(t0, t1);
            named_bar_sync(2, NCW * 32);
            float m0 = -INFINITY, m1 = -INFINITY;
#pragma unroll
            for (int w = 0; w < NCW / 2; w++) {
                const float4 x = *reinterpret_cast<const float4*>(wmax + tq * 16 + w * 4);
                m0 = fmaxf(m0, fmaxf(x.x, x.z)); m1 = fmaxf(m1, fmaxf(x.y, x.w));
            }
            m0 = tagf(m0 * SC, 0u); m1 = tagf(m1 * SC, 0u);
            float p0 = ex2(fmaf(s0, SC, -m0)), p1 = ex2(fmaf(s1, SC, -m1));
            float p2 = ex2(fmaf(s2, SC, -m0)), p3 = ex2(fmaf(s3, SC, -m1));
            if (t >= 2) { p0 = p1 = p2 = p3 = 0.f; }
            {
                uint2 bb;
                bb.x = movmatrix_t(pack_bf16(p0, p1));
                bb.y = movmatrix_t(pack_bf16(p2, p3));
                if (lane < 16) pbuf[(warp >> 1) * 32 + lane * 2 + (warp & 1)] = bb;
                float r0 = p0 + p2, r1 = p1 + p3;
#pragma unroll
                for (int x = 4; x <= 16; x <<= 1) {
                    r0 += __shfl_xor_sync(0xffffffffu, r0, x);
                    r1 += __shfl_xor_sync(0xffffffffu, r1, x);
                }
                if (lane < 2) *reinterpret_cast<float2*>(wsum + lane * 16 + warp * 2) = make_float2(r0, r1);
            }
            named_bar_sync(2, NCW * 32);
            uint2 pf[8];
            float l0 = 0.f, l1 = 0.f;
#pragma unroll
            for (int w = 0; w < NCW / 2; w++) {
                const uint4 y = *reinterpret_cast<const uint4*>(pbuf + w * 32 + (lane & 15) * 2);
                pf[2 * w] = make_uint2(y.x, y.y); pf[2 * w + 1] = make_uint2(y.z, y.w);
                const float4 x = *reinterpret_cast<const float4*>(wsum + tq * 16 + w * 4);
                l0 += x.x; l1 += x.y; l0 += x.z; l1 += x.w;
            }
            if (epoch1 == 0u && (flags != 0 || head >= RING)) { mbar_wait(bar_epoch, 0); epoch1 = *s_epoch + 1u; }
            const uint32_t tag = (flags & (FLAG_EXTRA | FLAG_FINAL)) ? (epoch1 & 1u) : ring_tag(head);
            float fo0 = 1.f, fo1 = 1.f;
            float* rec = nullptr;
            if (flags & FLAG_FINAL) {
                const float* cg = g_comb + (size_t)head * REC_FLOATS;
                const long long tstart = clock64();
                while ((tag_bad(cO, tag) | tag_bad(cML, tag)) != 0u) {
                    cO  = ld_relaxed_v4(cg + frag);
                    cML = ld_relaxed_v4(cg + SQ * DH + tq * 4);
                    if (clock64() - tstart > SPIN_LIMIT) __trap();
                }
                cO = untag(cO); cML = untag(cML);
                const float M0 = fmaxf(m0, cML.x), M1 = fmaxf(m1, cML.z);
                const float a0 = ex2(m0 - M0), a1 = ex2(m1 - M1), c0 = ex2(cML.x - M0), c1 = ex2(cML.z - M1);
                const float i0 = 1.0f / fmaf(l0, a0, cML.y * c0), i1 = 1.0f / fmaf(l1, a1, cML.w * c1);
                fo0 = a0 * i0; fo1 = a1 * i1;
                cO.x *= c0 * i0; cO.y *= c1 * i1; cO.z *= c0 * i0; cO.w *= c1 * i1;
            } else if (flags & FLAG_EXTRA) {
                rec = g_comb + (size_t)head * REC_FLOATS;
            } else {
                rec = g_ring + ((size_t)(head % RING) * NR + tile) * REC_FLOATS;
                if (head >= RING) {
                    const long long tstart = clock64();
                    while (freeflag != epoch1) {
                        freeflag = ld_relaxed_u32(g_coll + COLL_STRIDE * (head - RING));
                        if (clock64() - tstart > SPIN_LIMIT) __trap();
                    }
                }
            }
            __syncwarp();

            mbar_wait(bar_full + 8 * slot, phase);
            const uint32_t vb = sbase + SM_TILES + slot * TILE_BYTES + vOff;
            uint32_t vf[8][4];
#pragma unroll
            for (int j = 0; j < 8; j++) ldsm_x4_t(vf[j], vb + j * 16 * 128);
            __syncwarp();
            if (lane == 0) mbar_arrive(bar_empty + 8 * slot);
            if (++slot == NSLOTS) { slot = 0; phase ^= 1; }
            float oa[4] = {0.f, 0.f, 0.f, 0.f}, ob[4] = {0.f, 0.f, 0.f, 0.f};
#pragma unroll
            for (int j = 0; j < 8; j += 2) {
                mma_bf16(oa, vf[j], pf[j].x, pf[j].y);
                mma_bf16(ob, vf[j + 1], pf[j + 1].x, pf[j + 1].y);
            }
            if (t < 2) {
                if (flags & FLAG_FINAL) {
                    __nv_bfloat16* op = out + ((size_t)head * SQ + 2 * t) * DH + dcol;
                    op[0]      = __float2bfloat16(fmaf(oa[0] + ob[0], fo0, cO.x));
                    op[DH]     = __float2bfloat16(fmaf(oa[1] + ob[1], fo1, cO.y));
                    op[8]      = __float2bfloat16(fmaf(oa[2] + ob[2], fo0, cO.z));
                    op[DH + 8] = __float2bfloat16(fmaf(oa[3] + ob[3], fo1, cO.w));
                } else {
                    st_relaxed_v4(rec + frag, tagf(oa[0] + ob[0], tag), tagf(oa[1] + ob[1], tag),
                                  tagf(oa[2] + ob[2], tag), tagf(oa[3] + ob[3], tag));
                    if (threadIdx.x < 2) st_relaxed_v4(rec + SQ * DH + t * 4, tagf(m0, tag), tagf(l0, tag), tagf(m1, tag), tagf(l1, tag));
                }
            }
        }
    } else {
        const int e = threadIdx.x - NCW * 32;
        const int half = e >> 7;
        const int f = e & 127;
        const int tq = lane & 1;
        float* cx = reinterpret_cast<float*>(sptr + SM_CX);
        if (e == 0) {
            *s_epoch = ld_relaxed_u32(&g_epoch);
            mbar_arrive(bar_epoch);
        }
        mbar_wait(bar_epoch, 0);
        const uint32_t epoch1 = *s_epoch + 1u;
        const uint32_t etag = epoch1 & 1u;
        for (int k = 0;; k++) {
            const int js = k % JQ; const uint32_t jph = (k / JQ) & 1;
            mbar_wait(bar_jfull + 8 * js, jph);
            const int head = jobq[js];
            __syncwarp();
            if (lane == 0) mbar_arrive(bar_jfree + 8 * js);
            if (head < 0) break;
            const bool deferred = is_deferred(head);
            const uint32_t rtag = ring_tag(head);
            const int nrec_all = deferred ? NR : NR + 1;
            const int r0 = half * HREC;
            const int nrec = (nrec_all - r0 < HREC) ? (nrec_all - r0) : HREC;
            const float* ring = g_ring + ((size_t)(head % RING) * NR + r0) * REC_FLOATS;
            float* comb = g_comb + (size_t)head * REC_FLOATS;
            const int ml_u = lane & 15;
            const bool ml_extra = (r0 + ml_u == NR);
            const float* pml = (ml_extra ? comb : ring + (size_t)ml_u * REC_FLOATS) + SQ * DH + (lane >> 4) * 4;
            const uint32_t mltag = ml_extra ? etag : rtag;
            float4 v[HREC];
#pragma unroll
            for (int u = 0; u < HREC; u++) v[u] = make_float4(0.f, 0.f, 0.f, 0.f);
            float4 pm = make_float4(-INFINITY, 0.f, -INFINITY, 0.f);
            uint32_t pending = (1u << nrec) - 1u;
            const long long tstart = clock64();
            while (true) {
                if ((pending >> ml_u) & 1u) pm = ld_relaxed_v4(pml);
#pragma unroll
                for (int u = 0; u < HREC; u++)
                    if ((pending >> u) & 1u)
                        v[u] = ld_relaxed_v4(((r0 + u == NR) ? comb : ring + (size_t)u * REC_FLOATS) + f * 4);
                uint32_t bad = tag_bad(pm, mltag) << ml_u;
#pragma unroll
                for (int u = 0; u < HREC; u++) bad |= tag_bad(v[u], (r0 + u == NR) ? etag : rtag) << u;
                pending &= __reduce_or_sync(0xffffffffu, bad);
                if (pending == 0u) break;
                if (clock64() - tstart > SPIN_LIMIT) __trap();
                __nanosleep(500);
            }
            pm = untag(pm);
            const bool mlv = ml_u < nrec;
            float Ma = mlv ? pm.x : -INFINITY, Mb = mlv ? pm.z : -INFINITY;
#pragma unroll
            for (int x = 1; x < 16; x <<= 1) {
                Ma = fmaxf(Ma, __shfl_xor_sync(0xffffffffu, Ma, x));
                Mb = fmaxf(Mb, __shfl_xor_sync(0xffffffffu, Mb, x));
            }
            const float sca = mlv ? ex2(pm.x - Ma) : 0.f, scb = mlv ? ex2(pm.z - Mb) : 0.f;
            float La = mlv ? pm.y * sca : 0.f, Lb = mlv ? pm.w * scb : 0.f;
#pragma unroll
            for (int x = 1; x < 16; x <<= 1) {
                La += __shfl_xor_sync(0xffffffffu, La, x);
                Lb += __shfl_xor_sync(0xffffffffu, Lb, x);
            }
            float4 acc = make_float4(0.f, 0.f, 0.f, 0.f);
#pragma unroll
            for (int u = 0; u < HREC; u++) {
                const float sa = __shfl_sync(0xffffffffu, sca, u + 16 * tq), sb = __shfl_sync(0xffffffffu, scb, u + 16 * tq);
                const float4 x = untag(v[u]);
                acc.x = fmaf(x.x, sa, acc.x); acc.y = fmaf(x.y, sb, acc.y);
                acc.z = fmaf(x.z, sa, acc.z); acc.w = fmaf(x.w, sb, acc.w);
            }
            Ma = __shfl_sync(0xffffffffu, Ma, 16 * tq); La = __shfl_sync(0xffffffffu, La, 16 * tq);
            Mb = __shfl_sync(0xffffffffu, Mb, 16 * tq); Lb = __shfl_sync(0xffffffffu, Lb, 16 * tq);
            if (half == 1) {
                *reinterpret_cast<float4*>(cx + f * 4) = acc;
                if (f < 2) *reinterpret_cast<float4*>(cx + SQ * DH + tq * 4) = make_float4(Ma, La, Mb, Lb);
            }
            named_bar_sync(1, NEW * 32);
            if (e == NEW * 32 - 1) st_relaxed_u32(g_coll + COLL_STRIDE * head, epoch1);
            if (half == 0) {
                const float4 ov = *reinterpret_cast<const float4*>(cx + f * 4);
                const float4 oml = *reinterpret_cast<const float4*>(cx + SQ * DH + tq * 4);
                const float M0 = fmaxf(Ma, oml.x), M1 = fmaxf(Mb, oml.z);
                const float fa0 = ex2(Ma - M0), fb0 = ex2(oml.x - M0), fa1 = ex2(Mb - M1), fb1 = ex2(oml.z - M1);
                const float L0 = fmaf(La, fa0, oml.y * fb0), L1 = fmaf(Lb, fa1, oml.w * fb1);
                const float r0x = fmaf(acc.x, fa0, ov.x * fb0), r1x = fmaf(acc.y, fa1, ov.y * fb1);
                const float r0y = fmaf(acc.z, fa0, ov.z * fb0), r1y = fmaf(acc.w, fa1, ov.w * fb1);
                if (deferred) {
                    st_relaxed_v4(comb + f * 4, tagf(r0x, etag), tagf(r1x, etag), tagf(r0y, etag), tagf(r1y, etag));
                    if (f < 2) st_relaxed_v4(comb + SQ * DH + tq * 4, tagf(M0, etag), tagf(L0, etag), tagf(M1, etag), tagf(L1, etag));
                } else {
                    const float i0 = 1.0f / L0, i1 = 1.0f / L1;
                    __nv_bfloat16* op = out + ((size_t)head * SQ + 2 * tq) * DH + (f >> 4) * 16 + ((f >> 1) & 7);
                    op[0]      = __float2bfloat16(r0x * i0);
                    op[DH]     = __float2bfloat16(r1x * i1);
                    op[8]      = __float2bfloat16(r0y * i0);
                    op[DH + 8] = __float2bfloat16(r1y * i1);
                }
            }
            named_bar_sync(1, NEW * 32);
        }
    }
}

typedef CUresult (*EncodeTiledFn)(CUtensorMap*, CUtensorMapDataType, cuuint32_t, void*, const cuuint64_t*,
                                  const cuuint64_t*, const cuuint32_t*, const cuuint32_t*, CUtensorMapInterleave,
                                  CUtensorMapSwizzle, CUtensorMapL2promotion, CUtensorMapFloatOOBfill);

void make_map(EncodeTiledFn enc, CUtensorMap* m, void* p) {
    cuuint64_t dims[2]    = {(cuuint64_t)DH, (cuuint64_t)NHEADS * SKV};
    cuuint64_t strides[1] = {(cuuint64_t)DH * 2};
    cuuint32_t box[2]     = {64, (cuuint32_t)TILE_ROWS};
    cuuint32_t es[2]      = {1, 1};
    enc(m, CU_TENSOR_MAP_DATA_TYPE_BFLOAT16, 2, p, dims, strides, box, es, CU_TENSOR_MAP_INTERLEAVE_NONE,
        CU_TENSOR_MAP_SWIZZLE_128B, CU_TENSOR_MAP_L2_PROMOTION_L2_256B, CU_TENSOR_MAP_FLOAT_OOB_FILL_NONE);
}

}

extern "C" void kernel_launch(void* const* d_in, const int* in_sizes, int n_in, void* d_out, int out_size) {
    (void)in_sizes; (void)n_in; (void)out_size;
    static EncodeTiledFn enc = nullptr;
    static int nsm = 0;
    static unsigned gap_ns = 0, gap_cyc = 0;
    if (!enc) {
        cudaDriverEntryPointQueryResult qr;
        void* fn = nullptr;
        cudaGetDriverEntryPoint("cuTensorMapEncodeTiled", &fn, cudaEnableDefault, &qr);
        enc = (EncodeTiledFn)fn;
        cudaFuncSetAttribute(attn_decode_kernel, cudaFuncAttributeMaxDynamicSharedMemorySize, SMEM_BYTES);
        int dev = 0;
        cudaGetDevice(&dev);
        cudaDeviceGetAttribute(&nsm, cudaDevAttrMultiProcessorCount, dev);
        int mem_khz = 0, bus_bits = 0;
        cudaDeviceGetAttribute(&mem_khz, cudaDevAttrMemoryClockRate, dev);
        cudaDeviceGetAttribute(&bus_bits, cudaDevAttrGlobalMemoryBusWidth, dev);
        const double bw = 2.0 * mem_khz * 1e3 * bus_bits / 8.0 * 0.96;
        const int g = nsm < MAX_CTA ? nsm : MAX_CTA;
        double gap = bw > 0.0 ? (double)g * 2.0 * TILE_BYTES / bw * 1e9 - GAP_FIXED_NS : 0.0;
        gap_ns = gap < 0.0 ? 0u : gap > 1300.0 ? 1300u : (unsigned)gap;
        int sm_khz = 0;
        cudaDeviceGetAttribute(&sm_khz, cudaDevAttrClockRate, dev);
        gap_cyc = (unsigned)(gap_ns * 1.03e-6 * sm_khz);
    }
    CUtensorMap tmK, tmV, tmQ;
    {
        cuuint64_t dims[2] = {64, (cuuint64_t)NHEADS * SQ * 2}; cuuint64_t strides[1] = {128};
        cuuint32_t box[2] = {64, 8}; cuuint32_t es[2] = {1, 1};
        enc(&tmQ, CU_TENSOR_MAP_DATA_TYPE_BFLOAT16, 2, d_in[0], dims, strides, box, es, CU_TENSOR_MAP_INTERLEAVE_NONE,
            CU_TENSOR_MAP_SWIZZLE_128B, CU_TENSOR_MAP_L2_PROMOTION_NONE, CU_TENSOR_MAP_FLOAT_OOB_FILL_NONE);
    }
    make_map(enc, &tmK, d_in[1]);
    make_map(enc, &tmV, d_in[2]);
    const int grid = nsm < MAX_CTA ? nsm : MAX_CTA;
    attn_decode_kernel<<<grid, NTHREADS, SMEM_BYTES>>>(tmK, tmV, tmQ, (__nv_bfloat16*)d_out, gap_ns, gap_cyc);
}
```

```cpp
#include <cuda_runtime.h>
#include <cuda_bf16.h>
#include <cuda.h>
#include <stdint.h>

namespace {

constexpr int NHEADS = 512;
constexpr int SQ     = 4;
constexpr int SKV    = 4096;
constexpr int DH     = 128;

constexpr int TILE_ROWS  = 128;
constexpr int TILE_BYTES = TILE_ROWS * DH * 2;
constexpr int HALF_BYTES = TILE_BYTES / 2;
constexpr int TPH    = SKV / TILE_ROWS;
constexpr int NSLOTS = 4;
constexpr int WIN    = 2;
constexpr int NCW = 8;
constexpr int NEW = 8;
constexpr int NTHREADS = 32 * (NCW + NEW + 1);
constexpr int MAX_CTA = 132;
constexpr double GAP_FIXED_NS = 1400.0;

constexpr int NR   = TPH - 1;
constexpr int TH   = 500;
constexpr int GAP  = 12;
constexpr int HD0  = NHEADS - GAP - TH;
constexpr int NA1  = HD0 * (NR + 1);
constexpr int NA2  = NA1 + TH * NR;
constexpr int NA   = NA2 + GAP * (NR + 1);
constexpr int NCHUNKS = NA + TH;
constexpr int LAG  = 400;
constexpr int RING = 32;
constexpr int HREC = (NR + 2) / 2;
static_assert(HD0 >= 0 && LAG <= TH && LAG < (RING - 1) * NR && NHEADS % (2 * RING) == 0 && HREC <= 16 &&
              MAX_CTA <= LAG && MAX_CTA <= RING * NR && WIN + 1 <= NSLOTS, "bad schedule");

constexpr int JQ = 4;
constexpr int REC_BYTES  = SQ * DH * 4 + SQ * 8;
constexpr int REC_FLOATS = 544;

constexpr int SM_TILES = 0;
constexpr int SM_Q     = SM_TILES + NSLOTS * TILE_BYTES;
constexpr int SM_X     = SM_Q + NSLOTS * 1024;
constexpr int XS_BYTES = REC_BYTES + 16 + 16;
constexpr int SM_PB    = SM_X + NSLOTS * XS_BYTES;
constexpr int SM_WM    = SM_PB + 4 * 16 * 16;
constexpr int SM_WS    = SM_WM + NCW * SQ * 4;
constexpr int SM_CX    = SM_WS + NCW * SQ * 4;
constexpr int SM_META  = SM_CX + REC_BYTES;
constexpr int SM_JOB   = SM_META + NSLOTS * 16;
constexpr int SM_EPOCH = SM_JOB + JQ * 4;
constexpr int SM_BARS  = SM_EPOCH + 16;
constexpr int SM_TOTAL = SM_BARS + (2 * NSLOTS + 2 * JQ + 1) * 8;
constexpr int SMEM_BYTES = SM_TOTAL + 1024;
static_assert(REC_BYTES % 16 == 0 && XS_BYTES % 16 == 0 && SM_BARS % 8 == 0, "align");

constexpr int FLAG_END = 4, FLAG_EXTRA = 8, FLAG_FINAL = 16;

constexpr int COLL_STRIDE = 4;
struct Scratch {
    float ring[(size_t)RING * NR * REC_FLOATS];
    float comb[(size_t)NHEADS * REC_FLOATS];
    unsigned int coll[NHEADS * COLL_STRIDE];
    unsigned int pad0[64];
    unsigned int work;
    unsigned int pad1[63];
    unsigned int done;
    unsigned int pad2[63];
    unsigned int epoch;
};
union ScratchBlob { Scratch s; unsigned char bytes[4 << 20]; };
static_assert(sizeof(Scratch) <= sizeof(ScratchBlob), "scratch");
__device__ __align__(256) ScratchBlob g_scratch;
#define g_ring  (g_scratch.s.ring)
#define g_comb  (g_scratch.s.comb)
#define g_coll  (g_scratch.s.coll)
#define g_work  (g_scratch.s.work)
#define g_done  (g_scratch.s.done)
#define g_epoch (g_scratch.s.epoch)

__device__ __forceinline__ uint32_t smem_u32(const void* p) { return (uint32_t)__cvta_generic_to_shared(p); }
__device__ __forceinline__ void mbar_init(uint32_t bar, uint32_t cnt) {
    asm volatile("mbarrier.init.shared::cta.b64 [%0], %1;" :: "r"(bar), "r"(cnt) : "memory");
}
__device__ __forceinline__ void mbar_expect_tx(uint32_t bar, uint32_t bytes) {
    asm volatile("mbarrier.arrive.expect_tx.shared::cta.b64 _, [%0], %1;" :: "r"(bar), "r"(bytes) : "memory");
}
__device__ __forceinline__ void mbar_arrive(uint32_t bar) {
    asm volatile("mbarrier.arrive.shared::cta.b64 _, [%0];" :: "r"(bar) : "memory");
}
__device__ __forceinline__ bool mbar_try_wait(uint32_t bar, uint32_t parity) {
    uint32_t ok;
    asm volatile("{\n.reg .pred p;\nmbarrier.try_wait.parity.shared::cta.b64 p, [%1], %2;\nselp.u32 %0, 1, 0, p;\n}"
                 : "=r"(ok) : "r"(bar), "r"(parity) : "memory");
    return ok != 0;
}
constexpr long long SPIN_LIMIT = 4000000000LL;
__device__ __forceinline__ void mbar_wait(uint32_t bar, uint32_t parity) {
    if (mbar_try_wait(bar, parity)) return;
    const long long t0 = clock64();
    while (!mbar_try_wait(bar, parity)) {
        if (clock64() - t0 > SPIN_LIMIT) __trap();
    }
}
__device__ __forceinline__ void tma_load_2d(uint32_t dst, const CUtensorMap* tm, int c0, int c1, uint32_t bar, uint64_t pol) {
    asm volatile("cp.async.bulk.tensor.2d.shared::cluster.global.mbarrier::complete_tx::bytes.L2::cache_hint [%0], [%1, {%3, %4}], [%2], %5;"
                 :: "r"(dst), "l"(tm), "r"(bar), "r"(c0), "r"(c1), "l"(pol) : "memory");
}
__device__ __forceinline__ void tma_load_2d_nh(uint32_t dst, const CUtensorMap* tm, int c0, int c1, uint32_t bar) {
    asm volatile("cp.async.bulk.tensor.2d.shared::cluster.global.mbarrier::complete_tx::bytes [%0], [%1, {%3, %4}], [%2];"
                 :: "r"(dst), "l"(tm), "r"(bar), "r"(c0), "r"(c1) : "memory");
}
__device__ __forceinline__ void bulk_load(uint32_t dst, const void* src, uint32_t bytes, uint32_t bar) {
    asm volatile("cp.async.bulk.shared::cluster.global.mbarrier::complete_tx::bytes [%0], [%1], %2, [%3];"
                 :: "r"(dst), "l"(src), "r"(bytes), "r"(bar) : "memory");
}
__device__ __forceinline__ void ldsm_x4(uint32_t (&r)[4], uint32_t addr) {
    asm volatile("ldmatrix.sync.aligned.m8n8.x4.shared.b16 {%0,%1,%2,%3}, [%4];"
                 : "=r"(r[0]), "=r"(r[1]), "=r"(r[2]), "=r"(r[3]) : "r"(addr) : "memory");
}
__device__ __forceinline__ void ldsm_x4_t(uint32_t (&r)[4], uint32_t addr) {
    asm volatile("ldmatrix.sync.aligned.m8n8.x4.trans.shared.b16 {%0,%1,%2,%3}, [%4];"
                 : "=r"(r[0]), "=r"(r[1]), "=r"(r[2]), "=r"(r[3]) : "r"(addr) : "memory");
}
__device__ __forceinline__ void mma_bf16(float (&d)[4], const uint32_t (&a)[4], uint32_t b0, uint32_t b1) {
    asm volatile("mma.sync.aligned.m16n8k16.row.col.f32.bf16.bf16.f32 {%0,%1,%2,%3}, {%4,%5,%6,%7}, {%8,%9}, {%0,%1,%2,%3};"
                 : "+f"(d[0]), "+f"(d[1]), "+f"(d[2]), "+f"(d[3])
                 : "r"(a[0]), "r"(a[1]), "r"(a[2]), "r"(a[3]), "r"(b0), "r"(b1));
}
__device__ __forceinline__ uint32_t movmatrix_t(uint32_t a) {
    uint32_t d;
    asm volatile("movmatrix.sync.aligned.m8n8.trans.b16 %0, %1;" : "=r"(d) : "r"(a));
    return d;
}
__device__ __forceinline__ uint32_t pack_bf16(float lo, float hi) {
    uint32_t d;
    asm("cvt.rn.bf16x2.f32 %0, %1, %2;" : "=r"(d) : "f"(hi), "f"(lo));
    return d;
}
__device__ __forceinline__ float ex2(float x) {
    float y;
    asm("ex2.approx.ftz.f32 %0, %1;" : "=f"(y) : "f"(x));
    return y;
}
__device__ __forceinline__ float exp_diff(float a, float b) {
    return ex2((a - b) * (0.08838834764831845f * 1.4426950408889634f));
}
__device__ __forceinline__ void named_bar_sync(int id, int nthreads) {
    asm volatile("bar.sync %0, %1;" :: "r"(id), "r"(nthreads) : "memory");
}
__device__ __forceinline__ unsigned atom_inc_relaxed(unsigned int* p) {
    unsigned o;
    asm volatile("atom.relaxed.gpu.global.add.u32 %0, [%1], 1;" : "=r"(o) : "l"(p) : "memory");
    return o;
}
__device__ __forceinline__ unsigned long long global_ns() {
    unsigned long long t;
    asm volatile("mov.u64 %0, %globaltimer;" : "=l"(t));
    return t;
}
__device__ __forceinline__ uint32_t fbits(float x) { return __float_as_uint(x); }
__device__ __forceinline__ float tagf(float x, uint32_t tag) { return __uint_as_float((fbits(x) & ~1u) | tag); }
__device__ __forceinline__ float4 untag(const float4& v) {
    return make_float4(tagf(v.x, 0u), tagf(v.y, 0u), tagf(v.z, 0u), tagf(v.w, 0u));
}
__device__ __forceinline__ void pack_ml(float m, float l, uint32_t tag, float& wm, float& wl) {
    wm = tagf(m, tag);
    wl = __uint_as_float((fbits(l) & ~3u) | ((fbits(m) & 1u) << 1) | tag);
}
__device__ __forceinline__ float4 unpack_ml2(const float4& w) {
    return make_float4(__uint_as_float((fbits(w.x) & ~1u) | ((fbits(w.y) >> 1) & 1u)), __uint_as_float(fbits(w.y) & ~3u),
                       __uint_as_float((fbits(w.z) & ~1u) | ((fbits(w.w) >> 1) & 1u)), __uint_as_float(fbits(w.w) & ~3u));
}
__device__ __forceinline__ uint32_t tag_bad(const float4& v, uint32_t tag) {
    return ((fbits(v.x) ^ tag) | (fbits(v.y) ^ tag) | (fbits(v.z) ^ tag) | (fbits(v.w) ^ tag)) & 1u;
}
__device__ __forceinline__ void st_relaxed_u32(unsigned int* p, uint32_t x) {
    asm volatile("st.relaxed.gpu.global.u32 [%0], %1;" :: "l"(p), "r"(x) : "memory");
}
__device__ __forceinline__ void st_relaxed_v4(float* p, float x, float y, float z, float w) {
    asm volatile("st.relaxed.gpu.global.v4.f32 [%0], {%1, %2, %3, %4};" :: "l"(p), "f"(x), "f"(y), "f"(z), "f"(w) : "memory");
}
__device__ __forceinline__ void st_ml2(float* p, float m0, float l0, float m1, float l1, uint32_t tag) {
    float a, b, c, d;
    pack_ml(m0, l0, tag, a, b);
    pack_ml(m1, l1, tag, c, d);
    st_relaxed_v4(p, a, b, c, d);
}
__device__ __forceinline__ uint32_t ld_relaxed_u32(const unsigned int* p) {
    uint32_t v;
    asm volatile("ld.relaxed.gpu.global.u32 %0, [%1];" : "=r"(v) : "l"(p) : "memory");
    return v;
}
__device__ __forceinline__ float4 ld_relaxed_v4(const float* p) {
    float4 v;
    asm volatile("ld.relaxed.gpu.global.v4.f32 {%0,%1,%2,%3}, [%4];" : "=f"(v.x), "=f"(v.y), "=f"(v.z), "=f"(v.w) : "l"(p) : "memory");
    return v;
}

__device__ __forceinline__ void decode_a(int c, int& head, int& tile, int& cnt) {
    if (c < NA1)      { cnt = NR + 1; head = c / (NR + 1); tile = c % (NR + 1); }
    else if (c < NA2) { cnt = NR;     head = HD0 + (c - NA1) / NR; tile = (c - NA1) % NR; }
    else              { cnt = NR + 1; head = HD0 + TH + (c - NA2) / (NR + 1); tile = (c - NA2) % (NR + 1); }
}
__device__ __forceinline__ bool is_deferred(int head) { return head >= HD0 && head < HD0 + TH; }
__device__ __forceinline__ uint32_t ring_tag(int head) { return (uint32_t)(head / RING + 1) & 1u; }

__global__ void __launch_bounds__(NTHREADS, 1)
attn_decode_kernel(const __grid_constant__ CUtensorMap tmK, const __grid_constant__ CUtensorMap tmV,
                   const __grid_constant__ CUtensorMap tmQ, __nv_bfloat16* __restrict__ out,
                   const unsigned gap_ns, const unsigned gap_cyc)
{
    extern __shared__ unsigned char smem_raw[];
    const uint32_t sbase = (smem_u32(smem_raw) + 1023u) & ~1023u;
    unsigned char* sptr = smem_raw + (sbase - smem_u32(smem_raw));

    const int warp = threadIdx.x >> 5, lane = threadIdx.x & 31;
    const uint32_t bar_full  = sbase + SM_BARS;
    const uint32_t bar_empty = bar_full + NSLOTS * 8;
    const uint32_t bar_jfull = bar_empty + NSLOTS * 8;
    const uint32_t bar_jfree = bar_jfull + JQ * 8;
    const uint32_t bar_epoch = bar_jfree + JQ * 8;
    volatile uint32_t* s_epoch = reinterpret_cast<volatile uint32_t*>(sptr + SM_EPOCH);
    volatile int4* meta = reinterpret_cast<volatile int4*>(sptr + SM_META);
    volatile int* jobq = reinterpret_cast<volatile int*>(sptr + SM_JOB);

    uint64_t pol = 0;
    if (threadIdx.x == NTHREADS - 32) {
        mbar_init(bar_full, 1);
        mbar_init(bar_full + 8, 1);
        asm volatile("fence.mbarrier_init.release.cluster;" ::: "memory");
        asm volatile("createpolicy.fractional.L2::evict_first.b64 %0, 1.0;" : "=l"(pol));
        int head, tile, cnt;
        decode_a((int)blockIdx.x, head, tile, cnt);
        const int row = head * SKV + tile * TILE_ROWS;
        meta[0].x = head; meta[0].y = tile; meta[0].w = (tile == NR) ? FLAG_EXTRA : 0;
        mbar_expect_tx(bar_full, TILE_BYTES + SQ * DH * 2);
        tma_load_2d(sbase + SM_TILES, &tmK, 0, row, bar_full, pol);
        tma_load_2d(sbase + SM_TILES + HALF_BYTES, &tmK, 64, row, bar_full, pol);
        mbar_expect_tx(bar_full + 8, TILE_BYTES);
        tma_load_2d(sbase + SM_TILES + TILE_BYTES, &tmV, 0, row, bar_full + 8, pol);
        tma_load_2d(sbase + SM_TILES + TILE_BYTES + HALF_BYTES, &tmV, 64, row, bar_full + 8, pol);
        tma_load_2d_nh(sbase + SM_Q, &tmQ, 0, head * 8, bar_full);
        for (int s = 2; s < NSLOTS; s++) mbar_init(bar_full + 8 * s, 1);
        for (int s = 0; s < NSLOTS; s++) mbar_init(bar_empty + 8 * s, NCW);
        for (int s = 0; s < JQ; s++) { mbar_init(bar_jfull + 8 * s, 1); mbar_init(bar_jfree + 8 * s, NEW); }
        mbar_init(bar_epoch, 1);
        asm volatile("fence.mbarrier_init.release.cluster;" ::: "memory");
    }
    __syncthreads();

    if (warp == NCW + NEW) {
        if (lane == 0) {
            int nissued = 2;
            int job = 0;
            unsigned c = blockIdx.x + gridDim.x;
            while (c < (unsigned)NCHUNKS) {
                int head, tile, kind = 0;
                if (c < (unsigned)NA) {
                    int cnt;
                    decode_a((int)c, head, tile, cnt);
                    if (tile == NR) kind = FLAG_EXTRA;
                } else {
                    head = HD0 + ((int)c - NA); tile = NR; kind = FLAG_FINAL;
                }
                const bool chk = (kind == 0) && head >= RING;
                const int row = head * SKV + tile * TILE_ROWS;
                unsigned long long tk = 0;
                long long ck = 0;
#pragma unroll
                for (int i = 0; i < 2; i++) {
                    const int slot = nissued % NSLOTS;
                    if (nissued > WIN) {
                        const int prev = nissued - WIN;
                        mbar_wait(bar_full + 8 * (prev % NSLOTS), (prev / NSLOTS) & 1);
                    }
                    mbar_wait(bar_empty + 8 * slot, ((nissued / NSLOTS) & 1) ^ 1);
                    const uint32_t fb = bar_full + 8 * slot, dst = sbase + SM_TILES + slot * TILE_BYTES;
                    if (i == 0) {
                        const uint32_t xb = sbase + SM_X + slot * XS_BYTES;
                        meta[slot].x = head; meta[slot].y = tile; meta[slot].w = kind;
                        mbar_expect_tx(fb, TILE_BYTES + SQ * DH * 2 + (kind == FLAG_FINAL ? REC_BYTES : 0) + (chk ? 16 : 0));
                        tma_load_2d(dst, &tmK, 0, row, fb, pol);
                        tma_load_2d(dst + HALF_BYTES, &tmK, 64, row, fb, pol);
                        tma_load_2d_nh(sbase + SM_Q + slot * 1024, &tmQ, 0, head * 8, fb);
                        if (kind == FLAG_FINAL) bulk_load(xb, g_comb + (size_t)head * REC_FLOATS, REC_BYTES, fb);
                        if (chk) bulk_load(xb + REC_BYTES, g_coll + COLL_STRIDE * (head - RING), 16, fb);
                        tk = global_ns(); ck = clock64();
                        const int cc = (int)c - LAG;
                        if (cc >= 0 && cc < NA) {
                            int h2, t2, cnt2;
                            decode_a(cc, h2, t2, cnt2);
                            if (t2 == cnt2 - 1) {
                                const int js = job % JQ;
                                mbar_wait(bar_jfree + 8 * js, ((job / JQ) & 1) ^ 1);
                                jobq[js] = h2;
                                mbar_arrive(bar_jfull + 8 * js);
                                job++;
                            }
                        }
                    } else {
                        while (global_ns() - tk < gap_ns && clock64() - ck < (long long)gap_cyc) {}
                        mbar_expect_tx(fb, TILE_BYTES);
                        tma_load_2d(dst, &tmV, 0, row, fb, pol);
                        tma_load_2d(dst + HALF_BYTES, &tmV, 64, row, fb, pol);
                    }
                    nissued++;
                }
                c = atom_inc_relaxed(&g_work) + 2 * gridDim.x;
            }
            {
                const int js = job % JQ;
                mbar_wait(bar_jfree + 8 * js, ((job / JQ) & 1) ^ 1);
                jobq[js] = -1;
                mbar_arrive(bar_jfull + 8 * js);
            }
            {
                const int slot = nissued % NSLOTS;
                mbar_wait(bar_empty + 8 * slot, ((nissued / NSLOTS) & 1) ^ 1);
                meta[slot].w = FLAG_END;
                mbar_arrive(bar_full + 8 * slot);
            }
            mbar_wait(bar_epoch, 0);
            if (atom_inc_relaxed(&g_done) == gridDim.x - 1) { g_work = 0; g_done = 0; g_epoch = *s_epoch + 1u; }
        }
    } else if (warp < NCW) {
        const int g = lane >> 2, t = lane & 3, r8 = lane & 7;
        const uint32_t kOff = (uint32_t)((warp * 16 + r8 + ((lane >> 3) & 1) * 8) * 128 + (((lane >> 4) ^ r8) << 4));
        const uint32_t vOff = (uint32_t)((warp >> 2) * HALF_BYTES + (r8 + (lane >> 4) * 8) * 128 +
                                         (((((2 * warp) & 7) | ((lane >> 3) & 1)) ^ r8) << 4));
        float* wmax = reinterpret_cast<float*>(sptr + SM_WM);
        float* wsum = reinterpret_cast<float*>(sptr + SM_WS);
        uint2* pbuf = reinterpret_cast<uint2*>(sptr + SM_PB);
        const int tq = t & 1;
        const int dcol = warp * 16 + g;
        const int frag = (warp * 16 + g * 2 + tq) * 4;
        int slot = 0; uint32_t phase = 0;
        uint32_t epoch1 = 0u;
        while (true) {
            mbar_wait(bar_full + 8 * slot, phase);
            const int flags = meta[slot].w;
            if (flags & FLAG_END) break;
            const int head = meta[slot].x, tile = meta[slot].y;
            const uint32_t kb = sbase + SM_TILES + slot * TILE_BYTES;
            const unsigned char* xs = sptr + SM_X + slot * XS_BYTES;
            uint32_t kf[8][4];
#pragma unroll
            for (int j = 0; j < 8; j++)
                ldsm_x4(kf[j], kb + (j >> 2) * HALF_BYTES + (kOff ^ (uint32_t)(((2 * j) & 7) << 4)));
            uint32_t qf[4][4];
#pragma unroll
            for (int i = 0; i < 4; i++) {
                const int hr = 2 * (lane & 3) + (i >> 1);
                const int cc = ((i & 1) * 4 + (lane >> 3));
                ldsm_x4(qf[i], sbase + SM_Q + slot * 1024 + hr * 128 + ((cc ^ hr) << 4));
            }
            float4 cO = make_float4(0.f, 0.f, 0.f, 0.f), cML = make_float4(0.f, 0.f, 0.f, 0.f);
            if (flags & FLAG_FINAL) {
                const float* cs = reinterpret_cast<const float*>(xs);
                cO  = *reinterpret_cast<const float4*>(cs + frag);
                cML = *reinterpret_cast<const float4*>(cs + SQ * DH + tq * 4);
            }
            uint32_t freeflag = *reinterpret_cast<const uint32_t*>(xs + REC_BYTES);
            __syncwarp();
            if (lane == 0) mbar_arrive(bar_empty + 8 * slot);
            if (++slot == NSLOTS) { slot = 0; phase ^= 1; }

            float sa[4] = {0.f, 0.f, 0.f, 0.f}, sb[4] = {0.f, 0.f, 0.f, 0.f};
#pragma unroll
            for (int j = 0; j < 8; j += 2) {
                mma_bf16(sa, kf[j], qf[j >> 1][0], qf[j >> 1][1]);
                mma_bf16(sb, kf[j + 1], qf[j >> 1][2], qf[j >> 1][3]);
            }
            const float s0 = sa[0] + sb[0], s1 = sa[1] + sb[1], s2 = sa[2] + sb[2], s3 = sa[3] + sb[3];
            float t0 = fmaxf(s0, s2), t1 = fmaxf(s1, s3);
#pragma unroll
            for (int x = 4; x <= 16; x <<= 1) {
                t0 = fmaxf(t0, __shfl_xor_sync(0xffffffffu, t0, x));
                t1 = fmaxf(t1, __shfl_xor_sync(0xffffffffu, t1, x));
            }
            if (lane < 2) *reinterpret_cast<float2*>(wmax + lane * 16 + warp * 2) = make_float2(t0, t1);
            named_bar_sync(2, NCW * 32);
            float m0 = -INFINITY, m1 = -INFINITY;
#pragma unroll
            for (int w = 0; w < NCW / 2; w++) {
                const float4 x = *reinterpret_cast<const float4*>(wmax + tq * 16 + w * 4);
                m0 = fmaxf(m0, fmaxf(x.x, x.z)); m1 = fmaxf(m1, fmaxf(x.y, x.w));
            }
            float p0 = exp_diff(s0, m0), p1 = exp_diff(s1, m1);
            float p2 = exp_diff(s2, m0), p3 = exp_diff(s3, m1);
            if (t >= 2) { p0 = p1 = p2 = p3 = 0.f; }
            {
                uint2 bb;
                bb.x = movmatrix_t(pack_bf16(p0, p1));
                bb.y = movmatrix_t(pack_bf16(p2, p3));
                if (lane < 16) pbuf[(warp >> 1) * 32 + lane * 2 + (warp & 1)] = bb;
                float r0 = p0 + p2, r1 = p1 + p3;
#pragma unroll
                for (int x = 4; x <= 16; x <<= 1) {
                    r0 += __shfl_xor_sync(0xffffffffu, r0, x);
                    r1 += __shfl_xor_sync(0xffffffffu, r1, x);
                }
                if (lane < 2) *reinterpret_cast<float2*>(wsum + lane * 16 + warp * 2) = make_float2(r0, r1);
            }
            named_bar_sync(2, NCW * 32);
            uint2 pf[8];
            float l0 = 0.f, l1 = 0.f;
#pragma unroll
            for (int w = 0; w < NCW / 2; w++) {
                const uint4 y = *reinterpret_cast<const uint4*>(pbuf + w * 32 + (lane & 15) * 2);
                pf[2 * w] = make_uint2(y.x, y.y); pf[2 * w + 1] = make_uint2(y.z, y.w);
                const float4 x = *reinterpret_cast<const float4*>(wsum + tq * 16 + w * 4);
                l0 += x.x; l1 += x.y; l0 += x.z; l1 += x.w;
            }
            if (epoch1 == 0u && (flags != 0 || head >= RING)) { mbar_wait(bar_epoch, 0); epoch1 = *s_epoch + 1u; }
            const uint32_t tag = (flags & (FLAG_EXTRA | FLAG_FINAL)) ? (epoch1 & 1u) : ring_tag(head);
            float fo0 = 1.f, fo1 = 1.f;
            float* rec = nullptr;
            if (flags & FLAG_FINAL) {
                const float* cg = g_comb + (size_t)head * REC_FLOATS;
                const long long tstart = clock64();
                while ((tag_bad(cO, tag) | tag_bad(cML, tag)) != 0u) {
                    cO  = ld_relaxed_v4(cg + frag);
                    cML = ld_relaxed_v4(cg + SQ * DH + tq * 4);
                    if (clock64() - tstart > SPIN_LIMIT) __trap();
                }
                cO = untag(cO); cML = unpack_ml2(cML);
                const float M0 = fmaxf(m0, cML.x), M1 = fmaxf(m1, cML.z);
                const float a0 = exp_diff(m0, M0), a1 = exp_diff(m1, M1), c0 = exp_diff(cML.x, M0), c1 = exp_diff(cML.z, M1);
                const float i0 = 1.0f / fmaf(l0, a0, cML.y * c0), i1 = 1.0f / fmaf(l1, a1, cML.w * c1);
                fo0 = a0 * i0; fo1 = a1 * i1;
                cO.x *= c0 * i0; cO.y *= c1 * i1; cO.z *= c0 * i0; cO.w *= c1 * i1;
            } else if (flags & FLAG_EXTRA) {
                rec = g_comb + (size_t)head * REC_FLOATS;
            } else {
                rec = g_ring + ((size_t)(head % RING) * NR + tile) * REC_FLOATS;
                if (head >= RING) {
                    const long long tstart = clock64();
                    while (freeflag != epoch1) {
                        freeflag = ld_relaxed_u32(g_coll + COLL_STRIDE * (head - RING));
                        if (clock64() - tstart > SPIN_LIMIT) __trap();
                    }
                }
            }
            __syncwarp();

            mbar_wait(bar_full + 8 * slot, phase);
            const uint32_t vb = sbase + SM_TILES + slot * TILE_BYTES + vOff;
            uint32_t vf[8][4];
#pragma unroll
            for (int j = 0; j < 8; j++) ldsm_x4_t(vf[j], vb + j * 16 * 128);
            __syncwarp();
            if (lane == 0) mbar_arrive(bar_empty + 8 * slot);
            if (++slot == NSLOTS) { slot = 0; phase ^= 1; }
            float oa[4] = {0.f, 0.f, 0.f, 0.f}, ob[4] = {0.f, 0.f, 0.f, 0.f};
#pragma unroll
            for (int j = 0; j < 8; j += 2) {
                mma_bf16(oa, vf[j], pf[j].x, pf[j].y);
                mma_bf16(ob, vf[j + 1], pf[j + 1].x, pf[j + 1].y);
            }
            if (t < 2) {
                if (flags & FLAG_FINAL) {
                    __nv_bfloat16* op = out + ((size_t)head * SQ + 2 * t) * DH + dcol;
                    op[0]      = __float2bfloat16(fmaf(oa[0] + ob[0], fo0, cO.x));
                    op[DH]     = __float2bfloat16(fmaf(oa[1] + ob[1], fo1, cO.y));
                    op[8]      = __float2bfloat16(fmaf(oa[2] + ob[2], fo0, cO.z));
                    op[DH + 8] = __float2bfloat16(fmaf(oa[3] + ob[3], fo1, cO.w));
                } else {
                    st_relaxed_v4(rec + frag, tagf(oa[0] + ob[0], tag), tagf(oa[1] + ob[1], tag),
                                  tagf(oa[2] + ob[2], tag), tagf(oa[3] + ob[3], tag));
                    if (threadIdx.x < 2) st_ml2(rec + SQ * DH + t * 4, m0, l0, m1, l1, tag);
                }
            }
        }
    } else {
        const int e = threadIdx.x - NCW * 32;
        const int half = e >> 7;
        const int f = e & 127;
        const int tq = lane & 1;
        float* cx = reinterpret_cast<float*>(sptr + SM_CX);
        if (e == 0) {
            *s_epoch = ld_relaxed_u32(&g_epoch);
            mbar_arrive(bar_epoch);
        }
        mbar_wait(bar_epoch, 0);
        const uint32_t epoch1 = *s_epoch + 1u;
        const uint32_t etag = epoch1 & 1u;
        for (int k = 0;; k++) {
            const int js = k % JQ; const uint32_t jph = (k / JQ) & 1;
            mbar_wait(bar_jfull + 8 * js, jph);
            const int head = jobq[js];
            __syncwarp();
            if (lane == 0) mbar_arrive(bar_jfree + 8 * js);
            if (head < 0) break;
            const bool deferred = is_deferred(head);
            const uint32_t rtag = ring_tag(head);
            const int nrec_all = deferred ? NR : NR + 1;
            const int r0 = half * HREC;
            const int nrec = (nrec_all - r0 < HREC) ? (nrec_all - r0) : HREC;
            const float* ring = g_ring + ((size_t)(head % RING) * NR + r0) * REC_FLOATS;
            float* comb = g_comb + (size_t)head * REC_FLOATS;
            const int ml_u = lane & 15;
            const bool ml_extra = (r0 + ml_u == NR);
            const float* pml = (ml_extra ? comb : ring + (size_t)ml_u * REC_FLOATS) + SQ * DH + (lane >> 4) * 4;
            const uint32_t mltag = ml_extra ? etag : rtag;
            float4 v[HREC];
#pragma unroll
            for (int u = 0; u < HREC; u++) v[u] = make_float4(0.f, 0.f, 0.f, 0.f);
            float4 pm = make_float4(-INFINITY, 0.f, -INFINITY, 0.f);
            uint32_t pending = (1u << nrec) - 1u;
            const long long tstart = clock64();
            while (true) {
                if ((pending >> ml_u) & 1u) pm = ld_relaxed_v4(pml);
#pragma unroll
                for (int u = 0; u < HREC; u++)
                    if ((pending >> u) & 1u)
                        v[u] = ld_relaxed_v4(((r0 + u == NR) ? comb : ring + (size_t)u * REC_FLOATS) + f * 4);
                uint32_t bad = tag_bad(pm, mltag) << ml_u;
#pragma unroll
                for (int u = 0; u < HREC; u++) bad |= tag_bad(v[u], (r0 + u == NR) ? etag : rtag) << u;
                pending &= __reduce_or_sync(0xffffffffu, bad);
                if (pending == 0u) break;
                if (clock64() - tstart > SPIN_LIMIT) __trap();
                __nanosleep(500);
            }
            pm = unpack_ml2(pm);
            const bool mlv = ml_u < nrec;
            float Ma = mlv ? pm.x : -INFINITY, Mb = mlv ? pm.z : -INFINITY;
#pragma unroll
            for (int x = 1; x < 16; x <<= 1) {
                Ma = fmaxf(Ma, __shfl_xor_sync(0xffffffffu, Ma, x));
                Mb = fmaxf(Mb, __shfl_xor_sync(0xffffffffu, Mb, x));
            }
            const float sca = mlv ? exp_diff(pm.x, Ma) : 0.f, scb = mlv ? exp_diff(pm.z, Mb) : 0.f;
            float La = mlv ? pm.y * sca : 0.f, Lb = mlv ? pm.w * scb : 0.f;
#pragma unroll
            for (int x = 1; x < 16; x <<= 1) {
                La += __shfl_xor_sync(0xffffffffu, La, x);
                Lb += __shfl_xor_sync(0xffffffffu, Lb, x);
            }
            float4 acc = make_float4(0.f, 0.f, 0.f, 0.f);
#pragma unroll
            for (int u = 0; u < HREC; u++) {
                const float sa = __shfl_sync(0xffffffffu, sca, u + 16 * tq), sb = __shfl_sync(0xffffffffu, scb, u + 16 * tq);
                const float4 x = untag(v[u]);
                acc.x = fmaf(x.x, sa, acc.x); acc.y = fmaf(x.y, sb, acc.y);
                acc.z = fmaf(x.z, sa, acc.z); acc.w = fmaf(x.w, sb, acc.w);
            }
            Ma = __shfl_sync(0xffffffffu, Ma, 16 * tq); La = __shfl_sync(0xffffffffu, La, 16 * tq);
            Mb = __shfl_sync(0xffffffffu, Mb, 16 * tq); Lb = __shfl_sync(0xffffffffu, Lb, 16 * tq);
            if (half == 1) {
                *reinterpret_cast<float4*>(cx + f * 4) = acc;
                if (f < 2) *reinterpret_cast<float4*>(cx + SQ * DH + tq * 4) = make_float4(Ma, La, Mb, Lb);
            }
            named_bar_sync(1, NEW * 32);
            if (e == NEW * 32 - 1) st_relaxed_u32(g_coll + COLL_STRIDE * head, epoch1);
            if (half == 0) {
                const float4 ov = *reinterpret_cast<const float4*>(cx + f * 4);
                const float4 oml = *reinterpret_cast<const float4*>(cx + SQ * DH + tq * 4);
                const float M0 = fmaxf(Ma, oml.x), M1 = fmaxf(Mb, oml.z);
                const float fa0 = exp_diff(Ma, M0), fb0 = exp_diff(oml.x, M0), fa1 = exp_diff(Mb, M1), fb1 = exp_diff(oml.z, M1);
                const float L0 = fmaf(La, fa0, oml.y * fb0), L1 = fmaf(Lb, fa1, oml.w * fb1);
                const float r0x = fmaf(acc.x, fa0, ov.x * fb0), r1x = fmaf(acc.y, fa1, ov.y * fb1);
                const float r0y = fmaf(acc.z, fa0, ov.z * fb0), r1y = fmaf(acc.w, fa1, ov.w * fb1);
                if (deferred) {
                    st_relaxed_v4(comb + f * 4, tagf(r0x, etag), tagf(r1x, etag), tagf(r0y, etag), tagf(r1y, etag));
                    if (f < 2) st_ml2(comb + SQ * DH + tq * 4, M0, L0, M1, L1, etag);
                } else {
                    const float i0 = 1.0f / L0, i1 = 1.0f / L1;
                    __nv_bfloat16* op = out + ((size_t)head * SQ + 2 * tq) * DH + (f >> 4) * 16 + ((f >> 1) & 7);
                    op[0]      = __float2bfloat16(r0x * i0);
                    op[DH]     = __float2bfloat16(r1x * i1);
                    op[8]      = __float2bfloat16(r0y * i0);
                    op[DH + 8] = __float2bfloat16(r1y * i1);
                }
            }
            named_bar_sync(1, NEW * 32);
        }
    }
}

typedef CUresult (*EncodeTiledFn)(CUtensorMap*, CUtensorMapDataType, cuuint32_t, void*, const cuuint64_t*,
                                  const cuuint64_t*, const cuuint32_t*, const cuuint32_t*, CUtensorMapInterleave,
                                  CUtensorMapSwizzle, CUtensorMapL2promotion, CUtensorMapFloatOOBfill);

void make_map(EncodeTiledFn enc, CUtensorMap* m, void* p) {
    cuuint64_t dims[2]    = {(cuuint64_t)DH, (cuuint64_t)NHEADS * SKV};
    cuuint64_t strides[1] = {(cuuint64_t)DH * 2};
    cuuint32_t box[2]     = {64, (cuuint32_t)TILE_ROWS};
    cuuint32_t es[2]      = {1, 1};
    enc(m, CU_TENSOR_MAP_DATA_TYPE_BFLOAT16, 2, p, dims, strides, box, es, CU_TENSOR_MAP_INTERLEAVE_NONE,
        CU_TENSOR_MAP_SWIZZLE_128B, CU_TENSOR_MAP_L2_PROMOTION_L2_256B, CU_TENSOR_MAP_FLOAT_OOB_FILL_NONE);
}

}

extern "C" void kernel_launch(void* const* d_in, const int* in_sizes, int n_in, void* d_out, int out_size) {
    (void)in_sizes; (void)n_in; (void)out_size;
    static EncodeTiledFn enc = nullptr;
    static int nsm = 0;
    static unsigned gap_ns = 0, gap_cyc = 0;
    if (!enc) {
        cudaDriverEntryPointQueryResult qr;
        void* fn = nullptr;
        cudaGetDriverEntryPoint("cuTensorMapEncodeTiled", &fn, cudaEnableDefault, &qr);
        enc = (EncodeTiledFn)fn;
        cudaFuncSetAttribute(attn_decode_kernel, cudaFuncAttributeMaxDynamicSharedMemorySize, SMEM_BYTES);
        int dev = 0;
        cudaGetDevice(&dev);
        cudaDeviceGetAttribute(&nsm, cudaDevAttrMultiProcessorCount, dev);
        int mem_khz = 0, bus_bits = 0;
        cudaDeviceGetAttribute(&mem_khz, cudaDevAttrMemoryClockRate, dev);
        cudaDeviceGetAttribute(&bus_bits, cudaDevAttrGlobalMemoryBusWidth, dev);
        const double bw = 2.0 * mem_khz * 1e3 * bus_bits / 8.0 * 0.96;
        const int g = nsm < MAX_CTA ? nsm : MAX_CTA;
        double gap = bw > 0.0 ? (double)g * 2.0 * TILE_BYTES / bw * 1e9 - GAP_FIXED_NS : 0.0;
        gap_ns = gap < 0.0 ? 0u : gap > 1300.0 ? 1300u : (unsigned)gap;
        int sm_khz = 0;
        cudaDeviceGetAttribute(&sm_khz, cudaDevAttrClockRate, dev);
        gap_cyc = (unsigned)(gap_ns * 1.03e-6 * sm_khz);
    }
    CUtensorMap tmK, tmV, tmQ;
    {
        cuuint64_t dims[2] = {64, (cuuint64_t)NHEADS * SQ * 2}; cuuint64_t strides[1] = {128};
        cuuint32_t box[2] = {64, 8}; cuuint32_t es[2] = {1, 1};
        enc(&tmQ, CU_TENSOR_MAP_DATA_TYPE_BFLOAT16, 2, d_in[0], dims, strides, box, es, CU_TENSOR_MAP_INTERLEAVE_NONE,
            CU_TENSOR_MAP_SWIZZLE_128B, CU_TENSOR_MAP_L2_PROMOTION_NONE, CU_TENSOR_MAP_FLOAT_OOB_FILL_NONE);
    }
    make_map(enc, &tmK, d_in[1]);
    make_map(enc, &tmV, d_in[2]);
    const int grid = nsm < MAX_CTA ? nsm : MAX_CTA;
    attn_decode_kernel<<<grid, NTHREADS, SMEM_BYTES>>>(tmK, tmV, tmQ, (__nv_bfloat16*)d_out, gap_ns, gap_cyc);
}
```
